```python
import torch

def _softmax(x, axis=-1):
    return torch.softmax(x, dim=axis)
def _gelu(x):
    return torch.nn.functional.gelu(x, approximate="tanh")
def _silu(x):
    return torch.nn.functional.silu(x)
def _sigmoid(x):
    return torch.sigmoid(x)
def _layernorm(x, axis=-1, eps=1e-5):
    m = x.mean(dim=axis, keepdim=True)
    v = x.var(dim=axis, keepdim=True, unbiased=False)
    return (x - m) / torch.sqrt(v + eps)
def _scatter_add(tgt, idx, src, axis=0):
    return tgt.clone().index_add_(axis, idx, src)
def _segment_sum(src, seg, n):
    out = torch.zeros((n,) + src.shape[1:], dtype=src.dtype)
    return out.index_add_(0, seg, src)
def _pad(x, pw):
    flat = tuple(v for pair in reversed(pw) for v in pair)
    return torch.nn.functional.pad(x, flat)

kernel_name = 'recurrent_scan__softmax_full_mha__glu_gated_bilinear__prompt'

def setup_inputs():

    _w = (lambda a: (lambda t: t.to(torch.bfloat16) if t.is_floating_point() else t)(torch.as_tensor(a)))
    def _A_setup():
        B, S, D = 1, 2048, 512
        return {
            "x": _w((lambda *s: torch.randn(*s, dtype=torch.bfloat16) * 0.05)(B, S, D)),
            "wqkv": _w((lambda *s: torch.randn(*s, dtype=torch.bfloat16) * 0.2)(D, 3 * D)),
            "wo": _w((lambda *s: torch.randn(*s, dtype=torch.bfloat16) * 0.2)(D, D)),
        }
    _A_in = _A_setup()

    def _B_setup():
        B, S, D, F = 1, 2048, 512, 1792
        return {
            "x": _w((lambda *s: torch.randn(*s, dtype=torch.bfloat16) * 0.05)(B, S, D)),
            "w_gate": _w((lambda *s: torch.randn(*s, dtype=torch.bfloat16) * 0.1)(D, F) * (D ** -0.5)),
            "w_up": _w((lambda *s: torch.randn(*s, dtype=torch.bfloat16) * 0.1)(D, F) * (D ** -0.5)),
            "w_down": _w((lambda *s: torch.randn(*s, dtype=torch.bfloat16) * 0.1)(F, D) * (F ** -0.5)),
        }
    _B_in = _B_setup()

    return {
        "A_x": _A_in["x"],
        "A_wqkv": _A_in["wqkv"],
        "A_wo": _A_in["wo"],
        "B_x": _B_in["x"],
        "B_w_gate": _B_in["w_gate"],
        "B_w_up": _B_in["w_up"],
        "B_w_down": _B_in["w_down"],
    }

def reference(A_x, A_wqkv, A_wo, B_x, B_w_gate, B_w_up, B_w_down):
    def _A_ref(x, wqkv, wo):
        B, S, D = x.shape
        H = 32; Dh = D // H
        qkv = (lambda x, *d: x.permute(*d))((x @ wqkv).reshape(B, S, 3, H, Dh), 2, 0, 3, 1, 4)
        q, k, v = qkv[0], qkv[1], qkv[2]
        scale = Dh ** -0.5
        scores = torch.einsum("bhqd,bhkd->bhqk", q, k) * scale
        p = _softmax(scores, axis=-1)
        o = torch.einsum("bhqk,bhkd->bhqd", p, v)
        return (lambda x, *d: x.permute(*d))(o, 0, 2, 1, 3).reshape(B, S, D) @ wo

    def _B_ref(x, w_gate, w_up, w_down):
        g = torch.einsum("bsd,df->bsf", x, w_gate)
        u = torch.einsum("bsd,df->bsf", x, w_up)
        h = g * u
        return torch.einsum("bsf,fd->bsd", h, w_down)

    x = A_x
    xn = _layernorm(x, axis=-1)
    s = _A_ref(xn, A_wqkv, A_wo)
    g = _silu(_B_ref(xn, B_w_gate, B_w_up, B_w_down))
    return x + s * g
```

```cpp
#include <cuda_runtime.h>
#include <cuda_bf16.h>
#include <cuda.h>
#include <stdint.h>

namespace {

constexpr int SEQ = 2048, DM = 512, NH = 32, FF = 1792;

__device__ __align__(1024) uint8_t g_xn[SEQ * DM * 2];
__device__ __align__(1024) uint8_t g_qkv[NH * 6 * SEQ * 8 * 2];
__device__ __align__(1024) uint8_t g_h[SEQ * FF * 2];
__device__ __align__(1024) uint8_t g_o[SEQ * DM * 2];

__device__ __forceinline__ uint32_t smem_u32(const void* p) { return (uint32_t)__cvta_generic_to_shared(p); }
__device__ __forceinline__ void mbar_init(uint32_t bar, int cnt) {
    asm volatile("mbarrier.init.shared::cta.b64 [%0], %1;" ::"r"(bar), "r"(cnt) : "memory");
}
__device__ __forceinline__ void mbar_expect_tx(uint32_t bar, int bytes) {
    asm volatile("mbarrier.arrive.expect_tx.shared::cta.b64 _, [%0], %1;" ::"r"(bar), "r"(bytes) : "memory");
}
__device__ __forceinline__ void mbar_arrive(uint32_t bar) {
    asm volatile("mbarrier.arrive.shared::cta.b64 _, [%0];" ::"r"(bar) : "memory");
}
__device__ __forceinline__ void mbar_wait(uint32_t bar, int parity) {
    asm volatile(
        "{\n.reg .pred p;\n.reg .u32 c;\nmov.u32 c, 0;\n"
        "LW:\nmbarrier.try_wait.parity.shared::cta.b64 p, [%0], %1;\n@p bra LD;\n"
        "add.u32 c, c, 1;\nsetp.lt.u32 p, c, 4000000;\n@p bra LW;\ntrap;\nLD:\n}"
        ::"r"(bar), "r"(parity) : "memory");
}
__device__ __forceinline__ void fence_mbar_init() { asm volatile("fence.mbarrier_init.release.cluster;" ::: "memory"); }
__device__ __forceinline__ void fence_proxy_async() { asm volatile("fence.proxy.async;" ::: "memory"); }
__device__ __forceinline__ void bulk_g2s(uint32_t dst, const void* src, int bytes, uint32_t bar) {
    asm volatile("cp.async.bulk.shared::cluster.global.mbarrier::complete_tx::bytes [%0], [%1], %2, [%3];"
                 ::"r"(dst), "l"(src), "r"(bytes), "r"(bar) : "memory");
}
__device__ __forceinline__ void tma_2d(uint32_t dst, const CUtensorMap* map, int x, int y, uint32_t bar) {
    asm volatile("cp.async.bulk.tensor.2d.shared::cluster.global.mbarrier::complete_tx::bytes [%0], [%1, {%3, %4}], [%2];"
                 ::"r"(dst), "l"(map), "r"(bar), "r"(x), "r"(y) : "memory");
}
__device__ __forceinline__ void prefetch_map(const CUtensorMap* map) {
    asm volatile("prefetch.tensormap [%0];" ::"l"(map) : "memory");
}
__device__ __forceinline__ void pdl_wait() { asm volatile("griddepcontrol.wait;" ::: "memory"); }
__device__ __forceinline__ void pdl_launch() { asm volatile("griddepcontrol.launch_dependents;" ::: "memory"); }
__device__ __forceinline__ void wg_fence() { asm volatile("wgmma.fence.sync.aligned;" ::: "memory"); }
__device__ __forceinline__ void wg_commit() { asm volatile("wgmma.commit_group.sync.aligned;" ::: "memory"); }
template <int N> __device__ __forceinline__ void wg_wait() { asm volatile("wgmma.wait_group.sync.aligned %0;" ::"n"(N) : "memory"); }
template <int R> __device__ __forceinline__ void reg_inc() { asm volatile("setmaxnreg.inc.sync.aligned.u32 %0;" ::"n"(R)); }
template <int R> __device__ __forceinline__ void reg_dec() { asm volatile("setmaxnreg.dec.sync.aligned.u32 %0;" ::"n"(R)); }

__device__ __forceinline__ uint64_t make_desc(uint32_t addr, uint32_t lbo, uint32_t sbo, uint32_t swz) {
    return (uint64_t)((addr & 0x3FFFF) >> 4) | ((uint64_t)(lbo >> 4) << 16) | ((uint64_t)(sbo >> 4) << 32) | ((uint64_t)swz << 62);
}
__device__ __forceinline__ uint32_t pack_bf16(float lo, float hi) {
    uint32_t r;
    asm("cvt.rn.bf16x2.f32 %0, %1, %2;" : "=r"(r) : "f"(hi), "f"(lo));
    return r;
}
__device__ __forceinline__ float bf_lo(uint32_t v) { return __uint_as_float(v << 16); }
__device__ __forceinline__ float bf_hi(uint32_t v) { return __uint_as_float(v & 0xFFFF0000u); }
__device__ __forceinline__ float round_bf16(float x) { return __bfloat162float(__float2bfloat16_rn(x)); }
__device__ __forceinline__ uint32_t mul_bf16x2(uint32_t a, uint32_t b) {
    uint32_t r;
    asm("mul.rn.bf16x2 %0, %1, %2;" : "=r"(r) : "r"(a), "r"(b));
    return r;
}
__device__ __forceinline__ uint32_t sub_bf16x2(uint32_t a, uint32_t b) {
    uint32_t r;
    asm("sub.rn.bf16x2 %0, %1, %2;" : "=r"(r) : "r"(a), "r"(b));
    return r;
}

__device__ __forceinline__ void wgmma_ss_n256_bt(float (&d)[128], uint64_t da, uint64_t db, int acc) {
    asm volatile("{\n.reg .pred p;\nsetp.ne.b32 p, %130, 0;\n"
        "wgmma.mma_async.sync.aligned.m64n256k16.f32.bf16.bf16 {"
        "%0, %1, %2, %3, %4, %5, %6, %7, %8, %9, %10, %11, %12, %13, %14, %15, "
        "%16, %17, %18, %19, %20, %21, %22, %23, %24, %25, %26, %27, %28, %29, %30, %31, "
        "%32, %33, %34, %35, %36, %37, %38, %39, %40, %41, %42, %43, %44, %45, %46, %47, "
        "%48, %49, %50, %51, %52, %53, %54, %55, %56, %57, %58, %59, %60, %61, %62, %63, "
        "%64, %65, %66, %67, %68, %69, %70, %71, %72, %73, %74, %75, %76, %77, %78, %79, "
        "%80, %81, %82, %83, %84, %85, %86, %87, %88, %89, %90, %91, %92, %93, %94, %95, "
        "%96, %97, %98, %99, %100, %101, %102, %103, %104, %105, %106, %107, %108, %109, %110, %111, "
        "%112, %113, %114, %115, %116, %117, %118, %119, %120, %121, %122, %123, %124, %125, %126, %127"
        "}, %128, %129, p, 1, 1, 0, 1;\n}\n"
        :
        "+f"(d[0]), "+f"(d[1]), "+f"(d[2]), "+f"(d[3]), "+f"(d[4]), "+f"(d[5]), "+f"(d[6]), "+f"(d[7]),
        "+f"(d[8]), "+f"(d[9]), "+f"(d[10]), "+f"(d[11]), "+f"(d[12]), "+f"(d[13]), "+f"(d[14]), "+f"(d[15]),
        "+f"(d[16]), "+f"(d[17]), "+f"(d[18]), "+f"(d[19]), "+f"(d[20]), "+f"(d[21]), "+f"(d[22]), "+f"(d[23]),
        "+f"(d[24]), "+f"(d[25]), "+f"(d[26]), "+f"(d[27]), "+f"(d[28]), "+f"(d[29]), "+f"(d[30]), "+f"(d[31]),
        "+f"(d[32]), "+f"(d[33]), "+f"(d[34]), "+f"(d[35]), "+f"(d[36]), "+f"(d[37]), "+f"(d[38]), "+f"(d[39]),
        "+f"(d[40]), "+f"(d[41]), "+f"(d[42]), "+f"(d[43]), "+f"(d[44]), "+f"(d[45]), "+f"(d[46]), "+f"(d[47]),
        "+f"(d[48]), "+f"(d[49]), "+f"(d[50]), "+f"(d[51]), "+f"(d[52]), "+f"(d[53]), "+f"(d[54]), "+f"(d[55]),
        "+f"(d[56]), "+f"(d[57]), "+f"(d[58]), "+f"(d[59]), "+f"(d[60]), "+f"(d[61]), "+f"(d[62]), "+f"(d[63]),
        "+f"(d[64]), "+f"(d[65]), "+f"(d[66]), "+f"(d[67]), "+f"(d[68]), "+f"(d[69]), "+f"(d[70]), "+f"(d[71]),
        "+f"(d[72]), "+f"(d[73]), "+f"(d[74]), "+f"(d[75]), "+f"(d[76]), "+f"(d[77]), "+f"(d[78]), "+f"(d[79]),
        "+f"(d[80]), "+f"(d[81]), "+f"(d[82]), "+f"(d[83]), "+f"(d[84]), "+f"(d[85]), "+f"(d[86]), "+f"(d[87]),
        "+f"(d[88]), "+f"(d[89]), "+f"(d[90]), "+f"(d[91]), "+f"(d[92]), "+f"(d[93]), "+f"(d[94]), "+f"(d[95]),
        "+f"(d[96]), "+f"(d[97]), "+f"(d[98]), "+f"(d[99]), "+f"(d[100]), "+f"(d[101]), "+f"(d[102]), "+f"(d[103]),
        "+f"(d[104]), "+f"(d[105]), "+f"(d[106]), "+f"(d[107]), "+f"(d[108]), "+f"(d[109]), "+f"(d[110]), "+f"(d[111]),
        "+f"(d[112]), "+f"(d[113]), "+f"(d[114]), "+f"(d[115]), "+f"(d[116]), "+f"(d[117]), "+f"(d[118]), "+f"(d[119]),
        "+f"(d[120]), "+f"(d[121]), "+f"(d[122]), "+f"(d[123]), "+f"(d[124]), "+f"(d[125]), "+f"(d[126]), "+f"(d[127])
        : "l"(da), "l"(db), "r"(acc));
}
__device__ __forceinline__ void wgmma_ss_n128_bt(float (&d)[64], uint64_t da, uint64_t db, int acc) {
    asm volatile("{\n.reg .pred p;\nsetp.ne.b32 p, %66, 0;\n"
        "wgmma.mma_async.sync.aligned.m64n128k16.f32.bf16.bf16 {"
        "%0, %1, %2, %3, %4, %5, %6, %7, %8, %9, %10, %11, %12, %13, %14, %15, "
        "%16, %17, %18, %19, %20, %21, %22, %23, %24, %25, %26, %27, %28, %29, %30, %31, "
        "%32, %33, %34, %35, %36, %37, %38, %39, %40, %41, %42, %43, %44, %45, %46, %47, "
        "%48, %49, %50, %51, %52, %53, %54, %55, %56, %57, %58, %59, %60, %61, %62, %63"
        "}, %64, %65, p, 1, 1, 0, 1;\n}\n"
        :
        "+f"(d[0]), "+f"(d[1]), "+f"(d[2]), "+f"(d[3]), "+f"(d[4]), "+f"(d[5]), "+f"(d[6]), "+f"(d[7]),
        "+f"(d[8]), "+f"(d[9]), "+f"(d[10]), "+f"(d[11]), "+f"(d[12]), "+f"(d[13]), "+f"(d[14]), "+f"(d[15]),
        "+f"(d[16]), "+f"(d[17]), "+f"(d[18]), "+f"(d[19]), "+f"(d[20]), "+f"(d[21]), "+f"(d[22]), "+f"(d[23]),
        "+f"(d[24]), "+f"(d[25]), "+f"(d[26]), "+f"(d[27]), "+f"(d[28]), "+f"(d[29]), "+f"(d[30]), "+f"(d[31]),
        "+f"(d[32]), "+f"(d[33]), "+f"(d[34]), "+f"(d[35]), "+f"(d[36]), "+f"(d[37]), "+f"(d[38]), "+f"(d[39]),
        "+f"(d[40]), "+f"(d[41]), "+f"(d[42]), "+f"(d[43]), "+f"(d[44]), "+f"(d[45]), "+f"(d[46]), "+f"(d[47]),
        "+f"(d[48]), "+f"(d[49]), "+f"(d[50]), "+f"(d[51]), "+f"(d[52]), "+f"(d[53]), "+f"(d[54]), "+f"(d[55]),
        "+f"(d[56]), "+f"(d[57]), "+f"(d[58]), "+f"(d[59]), "+f"(d[60]), "+f"(d[61]), "+f"(d[62]), "+f"(d[63])
        : "l"(da), "l"(db), "r"(acc));
}
__device__ __forceinline__ void wgmma_qk_n128(float (&d)[64], uint64_t da, uint64_t db) {
    asm volatile(
        "wgmma.mma_async.sync.aligned.m64n128k16.f32.bf16.bf16 {"
        "%0, %1, %2, %3, %4, %5, %6, %7, %8, %9, %10, %11, %12, %13, %14, %15, "
        "%16, %17, %18, %19, %20, %21, %22, %23, %24, %25, %26, %27, %28, %29, %30, %31, "
        "%32, %33, %34, %35, %36, %37, %38, %39, %40, %41, %42, %43, %44, %45, %46, %47, "
        "%48, %49, %50, %51, %52, %53, %54, %55, %56, %57, %58, %59, %60, %61, %62, %63"
        "}, %64, %65, 0, 1, 1, 0, 0;\n"
        :
        "=f"(d[0]), "=f"(d[1]), "=f"(d[2]), "=f"(d[3]), "=f"(d[4]), "=f"(d[5]), "=f"(d[6]), "=f"(d[7]),
        "=f"(d[8]), "=f"(d[9]), "=f"(d[10]), "=f"(d[11]), "=f"(d[12]), "=f"(d[13]), "=f"(d[14]), "=f"(d[15]),
        "=f"(d[16]), "=f"(d[17]), "=f"(d[18]), "=f"(d[19]), "=f"(d[20]), "=f"(d[21]), "=f"(d[22]), "=f"(d[23]),
        "=f"(d[24]), "=f"(d[25]), "=f"(d[26]), "=f"(d[27]), "=f"(d[28]), "=f"(d[29]), "=f"(d[30]), "=f"(d[31]),
        "=f"(d[32]), "=f"(d[33]), "=f"(d[34]), "=f"(d[35]), "=f"(d[36]), "=f"(d[37]), "=f"(d[38]), "=f"(d[39]),
        "=f"(d[40]), "=f"(d[41]), "=f"(d[42]), "=f"(d[43]), "=f"(d[44]), "=f"(d[45]), "=f"(d[46]), "=f"(d[47]),
        "=f"(d[48]), "=f"(d[49]), "=f"(d[50]), "=f"(d[51]), "=f"(d[52]), "=f"(d[53]), "=f"(d[54]), "=f"(d[55]),
        "=f"(d[56]), "=f"(d[57]), "=f"(d[58]), "=f"(d[59]), "=f"(d[60]), "=f"(d[61]), "=f"(d[62]), "=f"(d[63])
        : "l"(da), "l"(db));
}
__device__ __forceinline__ void wgmma_pv_n24(float (&d)[12], uint32_t a0, uint32_t a1, uint32_t a2, uint32_t a3, uint64_t db) {
    asm volatile(
        "wgmma.mma_async.sync.aligned.m64n24k16.f32.bf16.bf16 {"
        "%0, %1, %2, %3, %4, %5, %6, %7, %8, %9, %10, %11"
        "}, {%12, %13, %14, %15}, %16, 1, 1, 1, 1;\n"
        :
        "+f"(d[0]), "+f"(d[1]), "+f"(d[2]), "+f"(d[3]), "+f"(d[4]), "+f"(d[5]), "+f"(d[6]), "+f"(d[7]),
        "+f"(d[8]), "+f"(d[9]), "+f"(d[10]), "+f"(d[11])
        : "r"(a0), "r"(a1), "r"(a2), "r"(a3), "l"(db));
}


__global__ void __launch_bounds__(256) ln_kernel(const __nv_bfloat16* __restrict__ x) {
    pdl_launch();
    const int warp = threadIdx.x >> 5, lane = threadIdx.x & 31, l16 = lane & 15;
    const int row = blockIdx.x * 16 + warp * 2 + (lane >> 4);
    const uint4* xr = reinterpret_cast<const uint4*>(x + (size_t)row * DM);
    uint32_t v[16];
#pragma unroll
    for (int i = 0; i < 4; i++) {
        uint4 t = __ldg(xr + l16 + 16 * i);
        v[4 * i] = t.x; v[4 * i + 1] = t.y; v[4 * i + 2] = t.z; v[4 * i + 3] = t.w;
    }
    float sum = 0.f;
#pragma unroll
    for (int i = 0; i < 16; i++) sum += bf_lo(v[i]) + bf_hi(v[i]);
#pragma unroll
    for (int o = 1; o < 16; o <<= 1) sum += __shfl_xor_sync(~0u, sum, o);
    const float mean = sum * (1.f / DM);
    float sq = 0.f;
#pragma unroll
    for (int i = 0; i < 16; i++) {
        float a = bf_lo(v[i]) - mean, b = bf_hi(v[i]) - mean;
        sq = fmaf(a, a, sq); sq = fmaf(b, b, sq);
    }
#pragma unroll
    for (int o = 1; o < 16; o <<= 1) sq += __shfl_xor_sync(~0u, sq, o);
    const float var = round_bf16(sq * (1.f / DM));
    const float sd = round_bf16(sqrtf(round_bf16(var + round_bf16(1e-5f))));
    const float rs = 1.f / sd;
    const uint32_t mean2 = pack_bf16(mean, mean);
    uint8_t* dst = g_xn + (size_t)(row >> 7) * 131072 + ((row & 127) >> 3) * 128 + (row & 7) * 16;
#pragma unroll
    for (int i = 0; i < 4; i++) {
        uint32_t w[4];
#pragma unroll
        for (int k = 0; k < 4; k++) {
            uint32_t d = sub_bf16x2(v[4 * i + k], mean2);
            w[k] = pack_bf16(bf_lo(d) * rs, bf_hi(d) * rs);
        }
        const int j = l16 + 16 * i;
        *reinterpret_cast<uint4*>(dst + (size_t)j * 2048) = make_uint4(w[0], w[1], w[2], w[3]);
    }
}

struct ProjMaps { CUtensorMap wqkv, wgate, wup; };
constexpr int PJ_STAGES = 3, PJ_STAGE_BYTES = 32768, PJ_A_BYTES = 131072;
constexpr int PJ_SMEM = PJ_A_BYTES + PJ_STAGES * PJ_STAGE_BYTES + 1024 + 256;

template <int N>
__device__ __forceinline__ void proj_mainloop(float (&acc)[N / 2], uint32_t a_base, uint32_t b_base, uint32_t bar_afull,
                                              uint32_t bar_full, uint32_t bar_empty, int& it, bool wait_a) {
#pragma unroll 1
    for (int kb = 0; kb < 8; kb++, it++) {
        const int st = it % PJ_STAGES;
        if (wait_a) mbar_wait(bar_afull + 8 * kb, 0);
        mbar_wait(bar_full + 8 * st, (it / PJ_STAGES) & 1);
        const uint64_t da = make_desc(a_base + kb * 16384, 2048, 128, 0);
        const uint64_t db = make_desc(b_base + st * PJ_STAGE_BYTES, 8192, 1024, 1);
        wg_fence();
#pragma unroll
        for (int k = 0; k < 4; k++) {
            if constexpr (N == 256) wgmma_ss_n256_bt(acc, da + k * 256, db + k * 128, (kb | k) != 0);
            else wgmma_ss_n128_bt(acc, da + k * 256, db + k * 128, (kb | k) != 0);
        }
        wg_commit();
        if (kb > 0) {
            wg_wait<1>();
            if ((threadIdx.x & 127) == 0) mbar_arrive(bar_empty + 8 * ((it - 1) % PJ_STAGES));
        }
    }
    wg_wait<0>();
    if ((threadIdx.x & 127) == 0) mbar_arrive(bar_empty + 8 * ((it - 1) % PJ_STAGES));
}

template <int N>
__device__ __forceinline__ void epi_qkv(const float (&acc)[N / 2], int unit0, int row_g, int t) {
#pragma unroll
    for (int i = 0; i < N / 8; i++) {
        const int u = unit0 + i / 8, il = i % 8;
        const int head = (u & 7) * 4 + (il >> 1), plane = (u >> 3) * 2 + (il & 1);
        uint8_t* p = g_qkv + ((size_t)(head * 6 + plane) * SEQ + row_g) * 16 + t * 4;
        *reinterpret_cast<uint32_t*>(p) = pack_bf16(acc[4 * i], acc[4 * i + 1]);
        *reinterpret_cast<uint32_t*>(p + 128) = pack_bf16(acc[4 * i + 2], acc[4 * i + 3]);
    }
}
template <int N>
__device__ __forceinline__ void epi_gu(const float (&acc)[N / 2], int f0, int m64, int warp, int lane) {
    constexpr int NG = N / 16;
#pragma unroll
    for (int i = 0; i < NG; i++) {
        const int f = f0 + 8 * i;
        uint8_t* p = g_h + ((size_t)(m64 * 28 + (f >> 6)) * 8 + ((f & 63) >> 3)) * 1024 + warp * 256 + lane * 4;
        const uint32_t lo = mul_bf16x2(pack_bf16(acc[4 * i], acc[4 * i + 1]), pack_bf16(acc[4 * (i + NG)], acc[4 * (i + NG) + 1]));
        const uint32_t hi = mul_bf16x2(pack_bf16(acc[4 * i + 2], acc[4 * i + 3]), pack_bf16(acc[4 * (i + NG) + 2], acc[4 * (i + NG) + 3]));
        *reinterpret_cast<uint32_t*>(p) = lo;
        *reinterpret_cast<uint32_t*>(p + 128) = hi;
    }
}

__global__ void __launch_bounds__(384, 1) proj_kernel(const __grid_constant__ ProjMaps maps) {
    extern __shared__ uint8_t smem_raw[];
    const uint32_t sbase = (smem_u32(smem_raw) + 1023) & ~1023u;
    const uint32_t a_base = sbase, b_base = sbase + PJ_A_BYTES;
    const uint32_t bar_afull = b_base + PJ_STAGES * PJ_STAGE_BYTES, bar_full = bar_afull + 64, bar_empty = bar_full + 8 * PJ_STAGES;
    const int tid = threadIdx.x;
    const int wg = __shfl_sync(~0u, tid >> 7, 0);
    const int mt = blockIdx.x & 15, g = blockIdx.x >> 4, pair = g >> 1;
    const bool odd = g & 1;
    if (tid == 0) {
        for (int i = 0; i < 8; i++) mbar_init(bar_afull + 8 * i, 1);
        for (int i = 0; i < PJ_STAGES; i++) { mbar_init(bar_full + 8 * i, 1); mbar_init(bar_empty + 8 * i, 2); }
        fence_mbar_init();
    }
    __syncthreads();
    pdl_launch();
    const int unit0 = 6 * pair + (odd ? 2 : 0);
    const int f1 = 448 * pair + (odd ? 256 : 0), f2 = f1 + 128;
    if (wg == 2) {
        reg_dec<40>();
        if (tid == 256) {
            prefetch_map(&maps.wqkv); prefetch_map(&maps.wgate); prefetch_map(&maps.wup);
            int it = 0;
            for (int tile = 0; tile < 3; tile++) {
                const int nbox = (tile == 1 || (tile == 0) == odd) ? 4 : 2;
                for (int kb = 0; kb < 8; kb++, it++) {
                    const int st = it % PJ_STAGES;
                    if (it == PJ_STAGES) {
                        pdl_wait();
                        for (int a = 0; a < 8; a++) {
                            mbar_expect_tx(bar_afull + 8 * a, 16384);
                            bulk_g2s(a_base + a * 16384, g_xn + (size_t)(mt * 8 + a) * 16384, 16384, bar_afull + 8 * a);
                        }
                    }
                    if (it >= PJ_STAGES) mbar_wait(bar_empty + 8 * st, ((it / PJ_STAGES) & 1) ^ 1);
                    const uint32_t dst = b_base + st * PJ_STAGE_BYTES, bar = bar_full + 8 * st;
                    mbar_expect_tx(bar, nbox * 8192);
                    if (tile == 0) {
                        for (int b = 0; b < nbox; b++) tma_2d(dst + b * 8192, &maps.wqkv, (unit0 + b) * 64, kb * 64, bar);
                    } else {
                        const int f = tile == 1 ? f1 : f2, hb = nbox >> 1;
                        for (int b = 0; b < hb; b++) {
                            tma_2d(dst + b * 8192, &maps.wgate, f + b * 64, kb * 64, bar);
                            tma_2d(dst + (hb + b) * 8192, &maps.wup, f + b * 64, kb * 64, bar);
                        }
                    }
                }
            }
        }
    } else {
        reg_inc<232>();
        const int warp = (tid >> 5) & 3, lane = tid & 31;
        const uint32_t a_wg = a_base + wg * 1024;
        const int m64 = mt * 2 + wg;
        const int row_g = m64 * 64 + warp * 16 + (lane >> 2);
        int it = 0;
        if (odd) {
            { float acc[128]; proj_mainloop<256>(acc, a_wg, b_base, bar_afull, bar_full, bar_empty, it, true); epi_qkv<256>(acc, unit0, row_g, lane & 3); }
            { float acc[128]; proj_mainloop<256>(acc, a_wg, b_base, bar_afull, bar_full, bar_empty, it, false); epi_gu<256>(acc, f1, m64, warp, lane); }
            { float acc[64]; proj_mainloop<128>(acc, a_wg, b_base, bar_afull, bar_full, bar_empty, it, false); epi_gu<128>(acc, f2, m64, warp, lane); }
        } else {
            { float acc[64]; proj_mainloop<128>(acc, a_wg, b_base, bar_afull, bar_full, bar_empty, it, true); epi_qkv<128>(acc, unit0, row_g, lane & 3); }
            { float acc[128]; proj_mainloop<256>(acc, a_wg, b_base, bar_afull, bar_full, bar_empty, it, false); epi_gu<256>(acc, f1, m64, warp, lane); }
            { float acc[128]; proj_mainloop<256>(acc, a_wg, b_base, bar_afull, bar_full, bar_empty, it, false); epi_gu<256>(acc, f2, m64, warp, lane); }
        }
    }
}

constexpr float ALPHA = 0.25f * 1.4426950408889634f;
constexpr float MAGIC = 12582912.f;
constexpr uint32_t POLY_MASK = 0x42524252u;
constexpr int AT_KV = 131072, AT_ONES = 32768, AT_Q = 16384;
constexpr int AT_SMEM = AT_KV + AT_ONES + AT_Q + 1024 + 256;
constexpr int PRING = 3;

__device__ __forceinline__ float ex2_mufu(float x) { float r; asm("ex2.approx.ftz.f32 %0, %1;" : "=f"(r) : "f"(x)); return r; }
__device__ __forceinline__ float ex2_fma(float s, float beta, float c254, float c3) {
    float y;
    asm("fma.rn.sat.f32 %0, %1, %2, %3;" : "=f"(y) : "f"(s), "f"(ALPHA / 254.f), "f"(beta));
    const float t = fmaf(y, c254, MAGIC - 126.f);
    const float r = t - (MAGIC - 126.f);
    const float f = fmaf(y, 254.f, -r);
    float p = fmaf(f, c3, 0.2426111251115799f);
    p = fmaf(p, f, 0.6932609677314758f);
    p = fmaf(p, f, 0.9999280571937561f);
    return __uint_as_float(__float_as_uint(p) + (__float_as_uint(t) << 23));
}
template <int KK>
__device__ __forceinline__ void softmax_pv(const float (&s)[64], uint32_t (&pp)[4 * PRING], float (&o)[12], float nm0, float nm1,
                                           float b0, float b1, uint64_t dv, float c254, float c3) {
    if constexpr (KK < 8) {
        float e[8];
#pragma unroll
        for (int i = 0; i < 8; i++) {
            const bool row1 = (i >> 1) & 1;
            const bool poly = (POLY_MASK >> ((KK & 3) * 8 + i)) & 1;
            e[i] = poly ? ex2_fma(s[8 * KK + i], row1 ? b1 : b0, c254, c3) : ex2_mufu(fmaf(s[8 * KK + i], ALPHA, row1 ? nm1 : nm0));
        }
        if constexpr (KK >= PRING) wg_wait<PRING - 1>();
        constexpr int R = 4 * (KK % PRING);
#pragma unroll
        for (int i = 0; i < 4; i++) pp[R + i] = pack_bf16(e[2 * i], e[2 * i + 1]);
        wg_fence();
        wgmma_pv_n24(o, pp[R], pp[R + 1], pp[R + 2], pp[R + 3], dv + KK * 16);
        wg_commit();
        softmax_pv<KK + 1>(s, pp, o, nm0, nm1, b0, b1, dv, c254, c3);
    }
}
__device__ __forceinline__ bool wg_any(bool pred, int bar_id) {
    uint32_t r;
    asm volatile("{\n.reg .pred p, q;\nsetp.ne.u32 p, %1, 0;\nbarrier.cta.red.or.aligned.pred q, %2, 128, p;\nselp.u32 %0, 1, 0, q;\n}"
                 : "=r"(r) : "r"((uint32_t)pred), "r"(bar_id) : "memory");
    return __shfl_sync(~0u, r, 0) != 0;
}

__global__ void __launch_bounds__(512, 1) attn_kernel(float c254, float c3) {
    extern __shared__ uint8_t smem_raw[];
    const uint32_t sbase = (smem_u32(smem_raw) + 1023) & ~1023u;
    uint8_t* sptr = smem_raw + (sbase - smem_u32(smem_raw));
    const uint32_t q_base = sbase + AT_KV + AT_ONES, bar_kv = q_base + AT_Q, bar_q = bar_kv + 128;
    const int tid = threadIdx.x;
    const int wg = __shfl_sync(~0u, tid >> 7, 0), warp = (tid >> 5) & 3, lane = tid & 31;
    const int head = blockIdx.x >> 2, qq = blockIdx.x & 3;
    if (tid == 0) {
        for (int i = 0; i < 17; i++) mbar_init(bar_kv + 8 * i, 1);
        fence_mbar_init();
    }
    for (int i = tid; i < AT_ONES / 16; i += 512)
        reinterpret_cast<uint4*>(sptr + AT_KV)[i] = make_uint4(0x3F803F80u, 0x3F803F80u, 0x3F803F80u, 0x3F803F80u);
    fence_proxy_async();
    __syncthreads();
    pdl_launch();
    if (tid == 0) {
        pdl_wait();
        const uint8_t* src = g_qkv + (size_t)head * 6 * 32768;
        mbar_expect_tx(bar_q, 16384);
        for (int p = 0; p < 2; p++) bulk_g2s(q_base + p * 8192, src + p * 32768 + qq * 8192, 8192, bar_q);
        for (int j = 0; j < 16; j++) {
            mbar_expect_tx(bar_kv + 8 * j, 8192);
            for (int p = 0; p < 4; p++) bulk_g2s(sbase + p * 32768 + j * 2048, src + (2 + p) * 32768 + j * 2048, 2048, bar_kv + 8 * j);
        }
    }
    const uint64_t dK = make_desc(sbase, 32768, 128, 0);
    const uint64_t dV = make_desc(sbase + 65536, 128, 32768, 0);
    mbar_wait(bar_q, 0);
#pragma unroll 1
    for (int qt = 0; qt < 2; qt++) {
        const int tile = wg * 2 + qt;
        const uint64_t dq = make_desc(q_base + tile * 1024, 8192, 128, 0);
        float s[64], o[12];
        uint32_t pp[4 * PRING];
#pragma unroll 1
        for (int attempt = 0; attempt < 2; attempt++) {
            float m0 = -INFINITY, m1 = -INFINITY;
            const int nmax = attempt ? 16 : 1;
#pragma unroll 1
            for (int j = nmax - 1; j >= 0; j--) {
                mbar_wait(bar_kv + 8 * j, 0);
                wg_fence(); wgmma_qk_n128(s, dq, dK + j * 128); wg_commit(); wg_wait<0>();
#pragma unroll
                for (int i = 0; i < 16; i++) {
                    m0 = fmaxf(m0, fmaxf(s[4 * i], s[4 * i + 1]));
                    m1 = fmaxf(m1, fmaxf(s[4 * i + 2], s[4 * i + 3]));
                }
            }
            m0 = fmaxf(m0, __shfl_xor_sync(~0u, m0, 1)); m0 = fmaxf(m0, __shfl_xor_sync(~0u, m0, 2));
            m1 = fmaxf(m1, __shfl_xor_sync(~0u, m1, 1)); m1 = fmaxf(m1, __shfl_xor_sync(~0u, m1, 2));
            const float room = attempt ? 0.f : 80.f;
            const float nm0 = -fmaf(m0, ALPHA, room), nm1 = -fmaf(m1, ALPHA, room);
            const float b0 = (126.f + nm0) * (1.f / 254.f), b1 = (126.f + nm1) * (1.f / 254.f);
#pragma unroll
            for (int i = 0; i < 12; i++) o[i] = 0.f;
            uint64_t dk = dK + 128, dv = dV;
#pragma unroll 1
            for (int j = 1; j < 16; j++) {
                softmax_pv<0>(s, pp, o, nm0, nm1, b0, b1, dv, c254, c3);
                mbar_wait(bar_kv + 8 * j, 0);
                wg_fence(); wgmma_qk_n128(s, dq, dk); wg_commit(); wg_wait<0>();
                dk += 128; dv += 128;
            }
            softmax_pv<0>(s, pp, o, nm0, nm1, b0, b1, dv, c254, c3);
            wg_wait<0>();
            if (attempt) break;
            bool ok = (o[8] < 1e36f) && (o[10] < 1e36f);
#pragma unroll
            for (int i = 0; i < 8; i++) ok = ok && (fabsf(o[i]) < INFINITY);
            if (!wg_any(!ok, 1 + wg)) break;
        }
        const float r0 = 1.f / o[8], r1 = 1.f / o[10];
        uint8_t* op = g_o + ((size_t)((qq * 8 + tile) * 8 + (head >> 2)) * 8 + (head & 3) * 2) * 1024 + warp * 256 + lane * 4;
        *reinterpret_cast<uint32_t*>(op) = pack_bf16(o[0] * r0, o[1] * r0);
        *reinterpret_cast<uint32_t*>(op + 128) = pack_bf16(o[2] * r1, o[3] * r1);
        *reinterpret_cast<uint32_t*>(op + 1024) = pack_bf16(o[4] * r0, o[5] * r0);
        *reinterpret_cast<uint32_t*>(op + 1024 + 128) = pack_bf16(o[6] * r1, o[7] * r1);
    }
}

struct OutMaps { CUtensorMap wdown, wo; };
constexpr int OUT_STAGES = 8, OUT_STAGE_BYTES = 24576;
constexpr int OUT_SMEM = OUT_STAGES * OUT_STAGE_BYTES + 1024 + 256;

__device__ __forceinline__ void out_mainloop(float (&acc)[64], int nkb, uint32_t base, uint32_t bar_full, uint32_t bar_empty, int& it) {
#pragma unroll 1
    for (int kb = 0; kb < nkb; kb++, it++) {
        const int st = it % OUT_STAGES;
        mbar_wait(bar_full + 8 * st, (it / OUT_STAGES) & 1);
        const uint64_t da = make_desc(base + st * OUT_STAGE_BYTES, 1024, 128, 0);
        const uint64_t db = make_desc(base + st * OUT_STAGE_BYTES + 8192, 8192, 1024, 1);
        wg_fence();
#pragma unroll
        for (int k = 0; k < 4; k++) wgmma_ss_n128_bt(acc, da + k * 128, db + k * 128, (kb | k) != 0);
        wg_commit();
        if (kb > 0) {
            wg_wait<1>();
            if (threadIdx.x == 0) mbar_arrive(bar_empty + 8 * ((it - 1) % OUT_STAGES));
        }
    }
    wg_wait<0>();
    if (threadIdx.x == 0) mbar_arrive(bar_empty + 8 * ((it - 1) % OUT_STAGES));
}

__global__ void __launch_bounds__(160, 1) out_kernel(const __grid_constant__ OutMaps maps, const __nv_bfloat16* __restrict__ x,
                                                     __nv_bfloat16* __restrict__ out) {
    extern __shared__ uint8_t smem_raw[];
    const uint32_t sbase = (smem_u32(smem_raw) + 1023) & ~1023u;
    const uint32_t bar_full = sbase + OUT_STAGES * OUT_STAGE_BYTES, bar_empty = bar_full + 8 * OUT_STAGES;
    const int tid = threadIdx.x;
    const int wid = __shfl_sync(~0u, tid >> 5, 0);
    const int m64 = blockIdx.x >> 2, nb = blockIdx.x & 3;
    if (tid == 0) {
        for (int i = 0; i < OUT_STAGES; i++) { mbar_init(bar_full + 8 * i, 1); mbar_init(bar_empty + 8 * i, 1); }
        fence_mbar_init();
    }
    __syncthreads();
    if (wid == 4) {
        if (tid == 128) {
            prefetch_map(&maps.wdown); prefetch_map(&maps.wo);
            for (int it = 0; it < OUT_STAGES; it++) {
                const uint32_t dst = sbase + it * OUT_STAGE_BYTES + 8192, bar = bar_full + 8 * it;
                mbar_expect_tx(bar, OUT_STAGE_BYTES);
                for (int b = 0; b < 2; b++) tma_2d(dst + b * 8192, &maps.wdown, nb * 128 + b * 64, it * 64, bar);
            }
            pdl_wait();
            for (int it = 0; it < 36; it++) {
                const int st = it % OUT_STAGES;
                const uint32_t dst = sbase + st * OUT_STAGE_BYTES, bar = bar_full + 8 * st;
                if (it >= OUT_STAGES) {
                    mbar_wait(bar_empty + 8 * st, ((it / OUT_STAGES) & 1) ^ 1);
                    mbar_expect_tx(bar, OUT_STAGE_BYTES);
                    for (int b = 0; b < 2; b++) {
                        if (it < 28) tma_2d(dst + 8192 + b * 8192, &maps.wdown, nb * 128 + b * 64, it * 64, bar);
                        else tma_2d(dst + 8192 + b * 8192, &maps.wo, nb * 128 + b * 64, (it - 28) * 64, bar);
                    }
                }
                const uint8_t* a = it < 28 ? g_h + (size_t)(m64 * 28 + it) * 8192 : g_o + (size_t)(m64 * 8 + it - 28) * 8192;
                bulk_g2s(dst, a, 8192, bar);
            }
        }
    } else {
        const int lane = tid & 31, t = lane & 3;
        const int row = m64 * 64 + wid * 16 + (lane >> 2);
        const uint32_t* xp = reinterpret_cast<const uint32_t*>(x + (size_t)row * DM + nb * 128) + t;
        uint32_t xv[32];
#pragma unroll
        for (int i = 0; i < 16; i++) { xv[2 * i] = __ldg(xp + 4 * i); xv[2 * i + 1] = __ldg(xp + 8 * (DM / 2) + 4 * i); }
        float dn[64], sa[64];
        int it = 0;
        out_mainloop(dn, 28, sbase, bar_full, bar_empty, it);
        out_mainloop(sa, 8, sbase, bar_full, bar_empty, it);
        uint32_t* op = reinterpret_cast<uint32_t*>(out + (size_t)row * DM + nb * 128) + t;
#pragma unroll
        for (int i = 0; i < 32; i++) {
            float r[2];
#pragma unroll
            for (int e = 0; e < 2; e++) {
                const float d = round_bf16(dn[2 * i + e]);
                const float gate = round_bf16(__fdividef(d, 1.f + __expf(-d)));
                const float pr = round_bf16(round_bf16(sa[2 * i + e]) * gate);
                r[e] = (e ? bf_hi(xv[i]) : bf_lo(xv[i])) + pr;
            }
            op[(i & 1) * 8 * (DM / 2) + 4 * (i >> 1)] = pack_bf16(r[0], r[1]);
        }
    }
}

typedef CUresult (*EncodeFn)(CUtensorMap*, CUtensorMapDataType, cuuint32_t, void*, const cuuint64_t*, const cuuint64_t*,
                             const cuuint32_t*, const cuuint32_t*, CUtensorMapInterleave, CUtensorMapSwizzle,
                             CUtensorMapL2promotion, CUtensorMapFloatOOBfill);

void make_weight_map(EncodeFn fn, CUtensorMap* m, const void* p, int rows, int cols) {
    cuuint64_t dims[2] = {(cuuint64_t)cols, (cuuint64_t)rows};
    cuuint64_t strides[1] = {(cuuint64_t)cols * 2};
    cuuint32_t box[2] = {64, 64}, es[2] = {1, 1};
    fn(m, CU_TENSOR_MAP_DATA_TYPE_BFLOAT16, 2, const_cast<void*>(p), dims, strides, box, es, CU_TENSOR_MAP_INTERLEAVE_NONE,
       CU_TENSOR_MAP_SWIZZLE_128B, CU_TENSOR_MAP_L2_PROMOTION_L2_256B, CU_TENSOR_MAP_FLOAT_OOB_FILL_NONE);
}

template <typename... KArgs, typename... Args>
void launch(void (*kern)(KArgs...), int grid, int block, int smem, bool pdl, Args... args) {
    cudaLaunchConfig_t cfg = {};
    cfg.gridDim = dim3(grid); cfg.blockDim = dim3(block); cfg.dynamicSmemBytes = smem; cfg.stream = cudaStreamPerThread;
    cudaLaunchAttribute attr[1];
    attr[0].id = cudaLaunchAttributeProgrammaticStreamSerialization;
    attr[0].val.programmaticStreamSerializationAllowed = 1;
    cfg.attrs = attr; cfg.numAttrs = pdl ? 1 : 0;
    cudaLaunchKernelEx(&cfg, kern, KArgs(args)...);
}

}

extern "C" void kernel_launch(void* const* d_in, const int* in_sizes, int n_in, void* d_out, int out_size) {
    (void)in_sizes; (void)n_in; (void)out_size;
    const __nv_bfloat16* x = (const __nv_bfloat16*)d_in[0];
    static EncodeFn encode = nullptr;
    if (!encode) {
        void* fn = nullptr;
        cudaDriverEntryPointQueryResult q;
        cudaGetDriverEntryPoint("cuTensorMapEncodeTiled", &fn, cudaEnableDefault, &q);
        encode = (EncodeFn)fn;
        cudaFuncSetAttribute(proj_kernel, cudaFuncAttributeMaxDynamicSharedMemorySize, PJ_SMEM);
        cudaFuncSetAttribute(attn_kernel, cudaFuncAttributeMaxDynamicSharedMemorySize, AT_SMEM);
        cudaFuncSetAttribute(out_kernel, cudaFuncAttributeMaxDynamicSharedMemorySize, OUT_SMEM);
    }
    ProjMaps pm;
    make_weight_map(encode, &pm.wqkv, d_in[1], DM, 3 * DM);
    make_weight_map(encode, &pm.wgate, d_in[4], DM, FF);
    make_weight_map(encode, &pm.wup, d_in[5], DM, FF);
    OutMaps om;
    make_weight_map(encode, &om.wdown, d_in[6], FF, DM);
    make_weight_map(encode, &om.wo, d_in[2], DM, DM);

    launch(ln_kernel, SEQ / 16, 256, 0, false, x);
    launch(proj_kernel, 128, 384, PJ_SMEM, true, pm);
    launch(attn_kernel, 128, 512, AT_SMEM, true, 254.f, 0.0551716685295105f);
    launch(out_kernel, 128, 160, OUT_SMEM, true, om, x, (__nv_bfloat16*)d_out);
}
```

```cpp
#include <cuda_runtime.h>
#include <cuda_bf16.h>
#include <cuda.h>
#include <stdint.h>

namespace {

constexpr int SEQ = 2048, DM = 512, NH = 32, FF = 1792;

__device__ __align__(1024) uint8_t g_xn[SEQ * DM * 2];
__device__ __align__(1024) uint8_t g_q[NH * 2 * SEQ * 8 * 2];
__device__ __align__(1024) uint8_t g_kv[NH * 4 * SEQ * 8 * 2];
__device__ __align__(1024) uint8_t g_h[SEQ * FF * 2];
__device__ __align__(1024) uint8_t g_o[SEQ * DM * 2];

#define TL(k, p) do {} while (0)
__device__ __forceinline__ uint32_t smem_u32(const void* p) { return (uint32_t)__cvta_generic_to_shared(p); }
__device__ __forceinline__ void mbar_init(uint32_t bar, int cnt) {
    asm volatile("mbarrier.init.shared::cta.b64 [%0], %1;" ::"r"(bar), "r"(cnt) : "memory");
}
__device__ __forceinline__ void mbar_expect_tx(uint32_t bar, int bytes) {
    asm volatile("mbarrier.arrive.expect_tx.shared::cta.b64 _, [%0], %1;" ::"r"(bar), "r"(bytes) : "memory");
}
__device__ __forceinline__ void mbar_arrive(uint32_t bar) {
    asm volatile("mbarrier.arrive.shared::cta.b64 _, [%0];" ::"r"(bar) : "memory");
}
__device__ __forceinline__ void mbar_wait(uint32_t bar, int parity) {
    asm volatile(
        "{\n.reg .pred p;\n.reg .u32 c;\nmov.u32 c, 0;\n"
        "LW:\nmbarrier.try_wait.parity.shared::cta.b64 p, [%0], %1;\n@p bra LD;\n"
        "add.u32 c, c, 1;\nsetp.lt.u32 p, c, 4000000;\n@p bra LW;\ntrap;\nLD:\n}"
        ::"r"(bar), "r"(parity) : "memory");
}
__device__ __forceinline__ void fence_mbar_init() { asm volatile("fence.mbarrier_init.release.cluster;" ::: "memory"); }
__device__ __forceinline__ void fence_proxy_async() { asm volatile("fence.proxy.async;" ::: "memory"); }
__device__ __forceinline__ void bulk_g2s(uint32_t dst, const void* src, int bytes, uint32_t bar) {
    asm volatile("cp.async.bulk.shared::cluster.global.mbarrier::complete_tx::bytes [%0], [%1], %2, [%3];"
                 ::"r"(dst), "l"(src), "r"(bytes), "r"(bar) : "memory");
}
__device__ __forceinline__ void tma_2d(uint32_t dst, const CUtensorMap* map, int x, int y, uint32_t bar) {
    asm volatile("cp.async.bulk.tensor.2d.shared::cluster.global.mbarrier::complete_tx::bytes [%0], [%1, {%3, %4}], [%2];"
                 ::"r"(dst), "l"(map), "r"(bar), "r"(x), "r"(y) : "memory");
}
__device__ __forceinline__ void prefetch_map(const CUtensorMap* map) {
    asm volatile("prefetch.tensormap [%0];" ::"l"(map) : "memory");
}
__device__ __forceinline__ void pdl_wait() { asm volatile("griddepcontrol.wait;" ::: "memory"); }
__device__ __forceinline__ void pdl_launch() { asm volatile("griddepcontrol.launch_dependents;" ::: "memory"); }
__device__ __forceinline__ void wg_fence() { asm volatile("wgmma.fence.sync.aligned;" ::: "memory"); }
__device__ __forceinline__ void wg_commit() { asm volatile("wgmma.commit_group.sync.aligned;" ::: "memory"); }
template <int N> __device__ __forceinline__ void wg_wait() { asm volatile("wgmma.wait_group.sync.aligned %0;" ::"n"(N) : "memory"); }
template <int R> __device__ __forceinline__ void reg_inc() { asm volatile("setmaxnreg.inc.sync.aligned.u32 %0;" ::"n"(R)); }
template <int R> __device__ __forceinline__ void reg_dec() { asm volatile("setmaxnreg.dec.sync.aligned.u32 %0;" ::"n"(R)); }

__device__ __forceinline__ uint64_t make_desc(uint32_t addr, uint32_t lbo, uint32_t sbo, uint32_t swz) {
    return (uint64_t)((addr & 0x3FFFF) >> 4) | ((uint64_t)(lbo >> 4) << 16) | ((uint64_t)(sbo >> 4) << 32) | ((uint64_t)swz << 62);
}
__device__ __forceinline__ uint32_t pack_bf16(float lo, float hi) {
    uint32_t r;
    asm("cvt.rn.bf16x2.f32 %0, %1, %2;" : "=r"(r) : "f"(hi), "f"(lo));
    return r;
}
__device__ __forceinline__ float bf_lo(uint32_t v) { return __uint_as_float(v << 16); }
__device__ __forceinline__ float bf_hi(uint32_t v) { return __uint_as_float(v & 0xFFFF0000u); }
__device__ __forceinline__ float round_bf16(float x) { return __bfloat162float(__float2bfloat16_rn(x)); }
__device__ __forceinline__ uint32_t mul_bf16x2(uint32_t a, uint32_t b) {
    uint32_t r;
    asm("mul.rn.bf16x2 %0, %1, %2;" : "=r"(r) : "r"(a), "r"(b));
    return r;
}
__device__ __forceinline__ uint32_t sub_bf16x2(uint32_t a, uint32_t b) {
    uint32_t r;
    asm("sub.rn.bf16x2 %0, %1, %2;" : "=r"(r) : "r"(a), "r"(b));
    return r;
}

__device__ __forceinline__ uint32_t add_bf16x2(uint32_t a, uint32_t b) {
    uint32_t r;
    asm("add.rn.bf16x2 %0, %1, %2;" : "=r"(r) : "r"(a), "r"(b));
    return r;
}
__device__ __forceinline__ float exp2_fast(float x) { float r; asm("ex2.approx.ftz.f32 %0, %1;" : "=f"(r) : "f"(x)); return r; }

__device__ __forceinline__ void wgmma_ss_n256_bt(float (&d)[128], uint64_t da, uint64_t db, int acc) {
    asm volatile("{\n.reg .pred p;\nsetp.ne.b32 p, %130, 0;\n"
        "wgmma.mma_async.sync.aligned.m64n256k16.f32.bf16.bf16 {"
        "%0, %1, %2, %3, %4, %5, %6, %7, %8, %9, %10, %11, %12, %13, %14, %15, "
        "%16, %17, %18, %19, %20, %21, %22, %23, %24, %25, %26, %27, %28, %29, %30, %31, "
        "%32, %33, %34, %35, %36, %37, %38, %39, %40, %41, %42, %43, %44, %45, %46, %47, "
        "%48, %49, %50, %51, %52, %53, %54, %55, %56, %57, %58, %59, %60, %61, %62, %63, "
        "%64, %65, %66, %67, %68, %69, %70, %71, %72, %73, %74, %75, %76, %77, %78, %79, "
        "%80, %81, %82, %83, %84, %85, %86, %87, %88, %89, %90, %91, %92, %93, %94, %95, "
        "%96, %97, %98, %99, %100, %101, %102, %103, %104, %105, %106, %107, %108, %109, %110, %111, "
        "%112, %113, %114, %115, %116, %117, %118, %119, %120, %121, %122, %123, %124, %125, %126, %127"
        "}, %128, %129, p, 1, 1, 0, 1;\n}\n"
        :
        "+f"(d[0]), "+f"(d[1]), "+f"(d[2]), "+f"(d[3]), "+f"(d[4]), "+f"(d[5]), "+f"(d[6]), "+f"(d[7]),
        "+f"(d[8]), "+f"(d[9]), "+f"(d[10]), "+f"(d[11]), "+f"(d[12]), "+f"(d[13]), "+f"(d[14]), "+f"(d[15]),
        "+f"(d[16]), "+f"(d[17]), "+f"(d[18]), "+f"(d[19]), "+f"(d[20]), "+f"(d[21]), "+f"(d[22]), "+f"(d[23]),
        "+f"(d[24]), "+f"(d[25]), "+f"(d[26]), "+f"(d[27]), "+f"(d[28]), "+f"(d[29]), "+f"(d[30]), "+f"(d[31]),
        "+f"(d[32]), "+f"(d[33]), "+f"(d[34]), "+f"(d[35]), "+f"(d[36]), "+f"(d[37]), "+f"(d[38]), "+f"(d[39]),
        "+f"(d[40]), "+f"(d[41]), "+f"(d[42]), "+f"(d[43]), "+f"(d[44]), "+f"(d[45]), "+f"(d[46]), "+f"(d[47]),
        "+f"(d[48]), "+f"(d[49]), "+f"(d[50]), "+f"(d[51]), "+f"(d[52]), "+f"(d[53]), "+f"(d[54]), "+f"(d[55]),
        "+f"(d[56]), "+f"(d[57]), "+f"(d[58]), "+f"(d[59]), "+f"(d[60]), "+f"(d[61]), "+f"(d[62]), "+f"(d[63]),
        "+f"(d[64]), "+f"(d[65]), "+f"(d[66]), "+f"(d[67]), "+f"(d[68]), "+f"(d[69]), "+f"(d[70]), "+f"(d[71]),
        "+f"(d[72]), "+f"(d[73]), "+f"(d[74]), "+f"(d[75]), "+f"(d[76]), "+f"(d[77]), "+f"(d[78]), "+f"(d[79]),
        "+f"(d[80]), "+f"(d[81]), "+f"(d[82]), "+f"(d[83]), "+f"(d[84]), "+f"(d[85]), "+f"(d[86]), "+f"(d[87]),
        "+f"(d[88]), "+f"(d[89]), "+f"(d[90]), "+f"(d[91]), "+f"(d[92]), "+f"(d[93]), "+f"(d[94]), "+f"(d[95]),
        "+f"(d[96]), "+f"(d[97]), "+f"(d[98]), "+f"(d[99]), "+f"(d[100]), "+f"(d[101]), "+f"(d[102]), "+f"(d[103]),
        "+f"(d[104]), "+f"(d[105]), "+f"(d[106]), "+f"(d[107]), "+f"(d[108]), "+f"(d[109]), "+f"(d[110]), "+f"(d[111]),
        "+f"(d[112]), "+f"(d[113]), "+f"(d[114]), "+f"(d[115]), "+f"(d[116]), "+f"(d[117]), "+f"(d[118]), "+f"(d[119]),
        "+f"(d[120]), "+f"(d[121]), "+f"(d[122]), "+f"(d[123]), "+f"(d[124]), "+f"(d[125]), "+f"(d[126]), "+f"(d[127])
        : "l"(da), "l"(db), "r"(acc));
}
__device__ __forceinline__ void wgmma_ss_n128_bt(float (&d)[64], uint64_t da, uint64_t db, int acc) {
    asm volatile("{\n.reg .pred p;\nsetp.ne.b32 p, %66, 0;\n"
        "wgmma.mma_async.sync.aligned.m64n128k16.f32.bf16.bf16 {"
        "%0, %1, %2, %3, %4, %5, %6, %7, %8, %9, %10, %11, %12, %13, %14, %15, "
        "%16, %17, %18, %19, %20, %21, %22, %23, %24, %25, %26, %27, %28, %29, %30, %31, "
        "%32, %33, %34, %35, %36, %37, %38, %39, %40, %41, %42, %43, %44, %45, %46, %47, "
        "%48, %49, %50, %51, %52, %53, %54, %55, %56, %57, %58, %59, %60, %61, %62, %63"
        "}, %64, %65, p, 1, 1, 0, 1;\n}\n"
        :
        "+f"(d[0]), "+f"(d[1]), "+f"(d[2]), "+f"(d[3]), "+f"(d[4]), "+f"(d[5]), "+f"(d[6]), "+f"(d[7]),
        "+f"(d[8]), "+f"(d[9]), "+f"(d[10]), "+f"(d[11]), "+f"(d[12]), "+f"(d[13]), "+f"(d[14]), "+f"(d[15]),
        "+f"(d[16]), "+f"(d[17]), "+f"(d[18]), "+f"(d[19]), "+f"(d[20]), "+f"(d[21]), "+f"(d[22]), "+f"(d[23]),
        "+f"(d[24]), "+f"(d[25]), "+f"(d[26]), "+f"(d[27]), "+f"(d[28]), "+f"(d[29]), "+f"(d[30]), "+f"(d[31]),
        "+f"(d[32]), "+f"(d[33]), "+f"(d[34]), "+f"(d[35]), "+f"(d[36]), "+f"(d[37]), "+f"(d[38]), "+f"(d[39]),
        "+f"(d[40]), "+f"(d[41]), "+f"(d[42]), "+f"(d[43]), "+f"(d[44]), "+f"(d[45]), "+f"(d[46]), "+f"(d[47]),
        "+f"(d[48]), "+f"(d[49]), "+f"(d[50]), "+f"(d[51]), "+f"(d[52]), "+f"(d[53]), "+f"(d[54]), "+f"(d[55]),
        "+f"(d[56]), "+f"(d[57]), "+f"(d[58]), "+f"(d[59]), "+f"(d[60]), "+f"(d[61]), "+f"(d[62]), "+f"(d[63])
        : "l"(da), "l"(db), "r"(acc));
}
__device__ __forceinline__ void wgmma_qk_n128(float (&d)[64], uint64_t da, uint64_t db) {
    asm volatile(
        "wgmma.mma_async.sync.aligned.m64n128k16.f32.bf16.bf16 {"
        "%0, %1, %2, %3, %4, %5, %6, %7, %8, %9, %10, %11, %12, %13, %14, %15, "
        "%16, %17, %18, %19, %20, %21, %22, %23, %24, %25, %26, %27, %28, %29, %30, %31, "
        "%32, %33, %34, %35, %36, %37, %38, %39, %40, %41, %42, %43, %44, %45, %46, %47, "
        "%48, %49, %50, %51, %52, %53, %54, %55, %56, %57, %58, %59, %60, %61, %62, %63"
        "}, %64, %65, 0, 1, 1, 0, 0;\n"
        :
        "=f"(d[0]), "=f"(d[1]), "=f"(d[2]), "=f"(d[3]), "=f"(d[4]), "=f"(d[5]), "=f"(d[6]), "=f"(d[7]),
        "=f"(d[8]), "=f"(d[9]), "=f"(d[10]), "=f"(d[11]), "=f"(d[12]), "=f"(d[13]), "=f"(d[14]), "=f"(d[15]),
        "=f"(d[16]), "=f"(d[17]), "=f"(d[18]), "=f"(d[19]), "=f"(d[20]), "=f"(d[21]), "=f"(d[22]), "=f"(d[23]),
        "=f"(d[24]), "=f"(d[25]), "=f"(d[26]), "=f"(d[27]), "=f"(d[28]), "=f"(d[29]), "=f"(d[30]), "=f"(d[31]),
        "=f"(d[32]), "=f"(d[33]), "=f"(d[34]), "=f"(d[35]), "=f"(d[36]), "=f"(d[37]), "=f"(d[38]), "=f"(d[39]),
        "=f"(d[40]), "=f"(d[41]), "=f"(d[42]), "=f"(d[43]), "=f"(d[44]), "=f"(d[45]), "=f"(d[46]), "=f"(d[47]),
        "=f"(d[48]), "=f"(d[49]), "=f"(d[50]), "=f"(d[51]), "=f"(d[52]), "=f"(d[53]), "=f"(d[54]), "=f"(d[55]),
        "=f"(d[56]), "=f"(d[57]), "=f"(d[58]), "=f"(d[59]), "=f"(d[60]), "=f"(d[61]), "=f"(d[62]), "=f"(d[63])
        : "l"(da), "l"(db));
}
__device__ __forceinline__ void wgmma_pv_n24(float (&d)[12], uint32_t a0, uint32_t a1, uint32_t a2, uint32_t a3, uint64_t db) {
    asm volatile(
        "wgmma.mma_async.sync.aligned.m64n24k16.f32.bf16.bf16 {"
        "%0, %1, %2, %3, %4, %5, %6, %7, %8, %9, %10, %11"
        "}, {%12, %13, %14, %15}, %16, 1, 1, 1, 1;\n"
        :
        "+f"(d[0]), "+f"(d[1]), "+f"(d[2]), "+f"(d[3]), "+f"(d[4]), "+f"(d[5]), "+f"(d[6]), "+f"(d[7]),
        "+f"(d[8]), "+f"(d[9]), "+f"(d[10]), "+f"(d[11])
        : "r"(a0), "r"(a1), "r"(a2), "r"(a3), "l"(db));
}

__global__ void __launch_bounds__(256) ln_kernel(const __nv_bfloat16* __restrict__ x) {
    pdl_launch();
    if (threadIdx.x == 0) TL(0, 0);
    const int warp = threadIdx.x >> 5, lane = threadIdx.x & 31, l16 = lane & 15;
    const int row = blockIdx.x * 16 + warp * 2 + (lane >> 4);
    const uint4* xr = reinterpret_cast<const uint4*>(x + (size_t)row * DM);
    uint32_t v[16];
#pragma unroll
    for (int i = 0; i < 4; i++) {
        uint4 t = __ldg(xr + l16 + 16 * i);
        v[4 * i] = t.x; v[4 * i + 1] = t.y; v[4 * i + 2] = t.z; v[4 * i + 3] = t.w;
    }
    float sum = 0.f;
#pragma unroll
    for (int i = 0; i < 16; i++) sum += bf_lo(v[i]) + bf_hi(v[i]);
#pragma unroll
    for (int o = 1; o < 16; o <<= 1) sum += __shfl_xor_sync(~0u, sum, o);
    const float mean = sum * (1.f / DM);
    float sq = 0.f;
#pragma unroll
    for (int i = 0; i < 16; i++) {
        float a = bf_lo(v[i]) - mean, b = bf_hi(v[i]) - mean;
        sq = fmaf(a, a, sq); sq = fmaf(b, b, sq);
    }
#pragma unroll
    for (int o = 1; o < 16; o <<= 1) sq += __shfl_xor_sync(~0u, sq, o);
    const float var = round_bf16(sq * (1.f / DM));
    const float sd = round_bf16(sqrtf(round_bf16(var + round_bf16(1e-5f))));
    const float rs = 1.f / sd;
    const uint32_t mean2 = pack_bf16(mean, mean);
    uint8_t* dst = g_xn + (size_t)(row >> 7) * 131072 + ((row & 127) >> 3) * 128 + (row & 7) * 16;
#pragma unroll
    for (int i = 0; i < 4; i++) {
        uint32_t w[4];
#pragma unroll
        for (int k = 0; k < 4; k++) {
            uint32_t d = sub_bf16x2(v[4 * i + k], mean2);
            w[k] = pack_bf16(bf_lo(d) * rs, bf_hi(d) * rs);
        }
        const int j = l16 + 16 * i;
        *reinterpret_cast<uint4*>(dst + (size_t)j * 2048) = make_uint4(w[0], w[1], w[2], w[3]);
    }
    if (threadIdx.x == 0) TL(0, 1);
}

struct ProjMaps { CUtensorMap wqkv, wgate, wup; };
constexpr int PJ_STAGES = 3, PJ_STAGE_BYTES = 32768, PJ_A_BYTES = 131072;
constexpr int PJ_SMEM = PJ_A_BYTES + PJ_STAGES * PJ_STAGE_BYTES + 1024 + 256;

template <int N>
__device__ __forceinline__ void proj_mainloop(float (&acc)[N / 2], uint32_t a_base, uint32_t b_base, uint32_t bar_afull,
                                              uint32_t bar_full, uint32_t bar_empty, int& it, bool wait_a) {
#pragma unroll 1
    for (int kb = 0; kb < 8; kb++, it++) {
        const int st = it % PJ_STAGES;
        if (wait_a) mbar_wait(bar_afull + 8 * kb, 0);
        mbar_wait(bar_full + 8 * st, (it / PJ_STAGES) & 1);
        const uint64_t da = make_desc(a_base + kb * 16384, 2048, 128, 0);
        const uint64_t db = make_desc(b_base + st * PJ_STAGE_BYTES, 8192, 1024, 1);
        wg_fence();
#pragma unroll
        for (int k = 0; k < 4; k++) {
            if constexpr (N == 256) wgmma_ss_n256_bt(acc, da + k * 256, db + k * 128, (kb | k) != 0);
            else wgmma_ss_n128_bt(acc, da + k * 256, db + k * 128, (kb | k) != 0);
        }
        wg_commit();
        if (kb > 0) {
            wg_wait<1>();
            if ((threadIdx.x & 127) == 0) mbar_arrive(bar_empty + 8 * ((it - 1) % PJ_STAGES));
        }
    }
    wg_wait<0>();
    if ((threadIdx.x & 127) == 0) mbar_arrive(bar_empty + 8 * ((it - 1) % PJ_STAGES));
}

template <int N>
__device__ __forceinline__ void epi_qkv(const float (&acc)[N / 2], int unit0, int row_g, int t) {
#pragma unroll
    for (int ub = 0; ub < N / 64; ub++) {
        const int u = unit0 + ub, type = u >> 3;
        uint8_t* base; int head_stride, plane_stride;
        if (type == 0) {
            base = g_q + (size_t)(u & 7) * 4 * 65536 + row_g * 16; head_stride = 65536; plane_stride = 32768;
        } else {
            base = g_kv + (size_t)(u & 7) * 4 * 131072 + (row_g >> 7) * 8192 + (type - 1) * 4096 + (row_g & 127) * 16;
            head_stride = 131072; plane_stride = 2048;
        }
        base += t * 4;
#pragma unroll
        for (int il = 0; il < 8; il++) {
            const int i = ub * 8 + il;
            uint8_t* p = base + (il >> 1) * head_stride + (il & 1) * plane_stride;
            *reinterpret_cast<uint32_t*>(p) = pack_bf16(acc[4 * i], acc[4 * i + 1]);
            *reinterpret_cast<uint32_t*>(p + 128) = pack_bf16(acc[4 * i + 2], acc[4 * i + 3]);
        }
    }
}
template <int N>
__device__ __forceinline__ void epi_gu(const float (&acc)[N / 2], int f0, int m64, int warp, int lane) {
    constexpr int NG = N / 16;
#pragma unroll
    for (int i = 0; i < NG; i++) {
        const int f = f0 + 8 * i;
        uint8_t* p = g_h + ((size_t)(m64 * 28 + (f >> 6)) * 8 + ((f & 63) >> 3)) * 1024 + warp * 256 + lane * 4;
        const uint32_t lo = mul_bf16x2(pack_bf16(acc[4 * i], acc[4 * i + 1]), pack_bf16(acc[4 * (i + NG)], acc[4 * (i + NG) + 1]));
        const uint32_t hi = mul_bf16x2(pack_bf16(acc[4 * i + 2], acc[4 * i + 3]), pack_bf16(acc[4 * (i + NG) + 2], acc[4 * (i + NG) + 3]));
        *reinterpret_cast<uint32_t*>(p) = lo;
        *reinterpret_cast<uint32_t*>(p + 128) = hi;
    }
}

__global__ void __launch_bounds__(384, 1) proj_kernel(const __grid_constant__ ProjMaps maps) {
    extern __shared__ uint8_t smem_raw[];
    const uint32_t sbase = (smem_u32(smem_raw) + 1023) & ~1023u;
    const uint32_t a_base = sbase, b_base = sbase + PJ_A_BYTES;
    const uint32_t bar_afull = b_base + PJ_STAGES * PJ_STAGE_BYTES, bar_full = bar_afull + 64, bar_empty = bar_full + 8 * PJ_STAGES;
    const int tid = threadIdx.x;
    const int wg = __shfl_sync(~0u, tid >> 7, 0);
    if (tid == 0) TL(1, 0);
    const int mt = blockIdx.x & 15, g = blockIdx.x >> 4, pair = g >> 1;
    const bool odd = g & 1;
    if (tid == 0) {
        for (int i = 0; i < 8; i++) mbar_init(bar_afull + 8 * i, 1);
        for (int i = 0; i < PJ_STAGES; i++) { mbar_init(bar_full + 8 * i, 1); mbar_init(bar_empty + 8 * i, 2); }
        fence_mbar_init();
    }
    __syncthreads();
    pdl_launch();
    const int unit0 = 6 * pair + (odd ? 2 : 0);
    const int f1 = 448 * pair + (odd ? 256 : 0), f2 = f1 + 128;
    if (wg == 2) {
        reg_dec<40>();
        if (tid == 256) {
            prefetch_map(&maps.wqkv); prefetch_map(&maps.wgate); prefetch_map(&maps.wup);
            int it = 0;
            for (int tile = 0; tile < 3; tile++) {
                const int nbox = (tile == 1 || (tile == 0) == odd) ? 4 : 2;
                for (int kb = 0; kb < 8; kb++, it++) {
                    const int st = it % PJ_STAGES;
                    if (it == PJ_STAGES) {
                        pdl_wait();
                        TL(1, 1);
                        for (int a = 0; a < 8; a++) {
                            mbar_expect_tx(bar_afull + 8 * a, 16384);
                            bulk_g2s(a_base + a * 16384, g_xn + (size_t)(mt * 8 + a) * 16384, 16384, bar_afull + 8 * a);
                        }
                    }
                    if (it >= PJ_STAGES) mbar_wait(bar_empty + 8 * st, ((it / PJ_STAGES) & 1) ^ 1);
                    const uint32_t dst = b_base + st * PJ_STAGE_BYTES, bar = bar_full + 8 * st;
                    mbar_expect_tx(bar, nbox * 8192);
                    if (tile == 0) {
                        for (int b = 0; b < nbox; b++) tma_2d(dst + b * 8192, &maps.wqkv, (unit0 + b) * 64, kb * 64, bar);
                    } else {
                        const int f = tile == 1 ? f1 : f2, hb = nbox >> 1;
                        for (int b = 0; b < hb; b++) {
                            tma_2d(dst + b * 8192, &maps.wgate, f + b * 64, kb * 64, bar);
                            tma_2d(dst + (hb + b) * 8192, &maps.wup, f + b * 64, kb * 64, bar);
                        }
                    }
                }
            }
        }
    } else {
        reg_inc<232>();
        const int warp = (tid >> 5) & 3, lane = tid & 31;
        const uint32_t a_wg = a_base + wg * 1024;
        const int m64 = mt * 2 + wg;
        const int row_g = m64 * 64 + warp * 16 + (lane >> 2);
        int it = 0;
        if (odd) {
            { float acc[128]; proj_mainloop<256>(acc, a_wg, b_base, bar_afull, bar_full, bar_empty, it, true); if (tid == 0) TL(1, 2); epi_qkv<256>(acc, unit0, row_g, lane & 3); if (tid == 0) TL(1, 3); }
            { float acc[128]; proj_mainloop<256>(acc, a_wg, b_base, bar_afull, bar_full, bar_empty, it, false); if (tid == 0) TL(1, 4); epi_gu<256>(acc, f1, m64, warp, lane); if (tid == 0) TL(1, 5); }
            { float acc[64]; proj_mainloop<128>(acc, a_wg, b_base, bar_afull, bar_full, bar_empty, it, false); if (tid == 0) TL(1, 6); epi_gu<128>(acc, f2, m64, warp, lane); if (tid == 0) TL(1, 7); }
        } else {
            { float acc[64]; proj_mainloop<128>(acc, a_wg, b_base, bar_afull, bar_full, bar_empty, it, true); if (tid == 0) TL(1, 2); epi_qkv<128>(acc, unit0, row_g, lane & 3); if (tid == 0) TL(1, 3); }
            { float acc[128]; proj_mainloop<256>(acc, a_wg, b_base, bar_afull, bar_full, bar_empty, it, false); if (tid == 0) TL(1, 4); epi_gu<256>(acc, f1, m64, warp, lane); if (tid == 0) TL(1, 5); }
            { float acc[128]; proj_mainloop<256>(acc, a_wg, b_base, bar_afull, bar_full, bar_empty, it, false); if (tid == 0) TL(1, 6); epi_gu<256>(acc, f2, m64, warp, lane); if (tid == 0) TL(1, 7); }
        }
    }
}

constexpr float ALPHA = 0.25f * 1.4426950408889634f;
constexpr float MAGIC = 12582912.f;
constexpr uint32_t POLY_MASK = 0x42524252u;
constexpr int AT_TILE = 10240, AT_KV = 16 * AT_TILE, AT_Q = 16384;
constexpr int AT_SMEM = AT_KV + AT_Q + 1024 + 256;
constexpr int PRING = 3;

__device__ __forceinline__ float ex2_fma(float s, float beta, float c254, float c3) {
    float y;
    asm("fma.rn.sat.f32 %0, %1, %2, %3;" : "=f"(y) : "f"(s), "f"(ALPHA / 254.f), "f"(beta));
    const float t = fmaf(y, c254, MAGIC - 126.f);
    const float r = t - (MAGIC - 126.f);
    const float f = fmaf(y, 254.f, -r);
    float p = fmaf(f, c3, 0.2426111251115799f);
    p = fmaf(p, f, 0.6932609677314758f);
    p = fmaf(p, f, 0.9999280571937561f);
    return __uint_as_float(__float_as_uint(p) + (__float_as_uint(t) << 23));
}
template <int KK>
__device__ __forceinline__ void softmax_pv(const float (&s)[64], uint32_t (&pp)[4 * PRING], float (&o)[12], float nm0, float nm1,
                                           float b0, float b1, uint64_t dv, float c254, float c3) {
    if constexpr (KK < 8) {
        float e[8];
#pragma unroll
        for (int i = 0; i < 8; i++) {
            const bool row1 = (i >> 1) & 1;
            const bool poly = (POLY_MASK >> ((KK & 3) * 8 + i)) & 1;
            e[i] = poly ? ex2_fma(s[8 * KK + i], row1 ? b1 : b0, c254, c3) : exp2_fast(fmaf(s[8 * KK + i], ALPHA, row1 ? nm1 : nm0));
        }
        if constexpr (KK >= PRING) wg_wait<PRING - 1>();
        constexpr int R = 4 * (KK % PRING);
#pragma unroll
        for (int i = 0; i < 4; i++) pp[R + i] = pack_bf16(e[2 * i], e[2 * i + 1]);
        wg_fence();
        wgmma_pv_n24(o, pp[R], pp[R + 1], pp[R + 2], pp[R + 3], dv + KK * 16);
        wg_commit();
        softmax_pv<KK + 1>(s, pp, o, nm0, nm1, b0, b1, dv, c254, c3);
    }
}
__device__ __forceinline__ bool wg_any(bool pred, int bar_id) {
    uint32_t r;
    asm volatile("{\n.reg .pred p, q;\nsetp.ne.u32 p, %1, 0;\nbarrier.cta.red.or.aligned.pred q, %2, 128, p;\nselp.u32 %0, 1, 0, q;\n}"
                 : "=r"(r) : "r"((uint32_t)pred), "r"(bar_id) : "memory");
    return __shfl_sync(~0u, r, 0) != 0;
}

__global__ void __launch_bounds__(512, 1) attn_kernel(float c254, float c3) {
    extern __shared__ uint8_t smem_raw[];
    const uint32_t sbase = (smem_u32(smem_raw) + 1023) & ~1023u;
    uint8_t* sptr = smem_raw + (sbase - smem_u32(smem_raw));
    const uint32_t q_base = sbase + AT_KV, bar_kv = q_base + AT_Q, bar_q = bar_kv + 128;
    const int tid = threadIdx.x;
    const int wg = __shfl_sync(~0u, tid >> 7, 0), warp = (tid >> 5) & 3, lane = tid & 31;
    const int head = blockIdx.x >> 2, qq = blockIdx.x & 3;
    if (tid == 0) TL(2, 0);
    if (tid == 0) {
        for (int i = 0; i < 17; i++) mbar_init(bar_kv + 8 * i, 1);
        fence_mbar_init();
    }
    for (int i = tid; i < 16 * 128; i += 512)
        reinterpret_cast<uint4*>(sptr + (i >> 7) * AT_TILE + 8192)[i & 127] = make_uint4(0x3F803F80u, 0x3F803F80u, 0x3F803F80u, 0x3F803F80u);
    fence_proxy_async();
    __syncthreads();
    pdl_launch();
    if (warp == 0 && lane == 0) {
        pdl_wait();
        if (tid == 0) {
            TL(2, 1);
            mbar_expect_tx(bar_q, 16384);
            for (int p = 0; p < 2; p++) bulk_g2s(q_base + p * 8192, g_q + (size_t)head * 65536 + p * 32768 + qq * 8192, 8192, bar_q);
        }
        for (int j = wg; j < 16; j += 4) {
            mbar_expect_tx(bar_kv + 8 * j, 8192);
            bulk_g2s(sbase + j * AT_TILE, g_kv + (size_t)head * 131072 + j * 8192, 8192, bar_kv + 8 * j);
        }
    }
    const uint64_t dK = make_desc(sbase, 2048, 128, 0);
    const uint64_t dV = make_desc(sbase + 4096, 128, 2048, 0);
    mbar_wait(bar_q, 0);
    if (tid == 0) TL(2, 2);
#pragma unroll 1
    for (int qt = 0; qt < 2; qt++) {
        const int tile = wg * 2 + qt;
        const uint64_t dq = make_desc(q_base + tile * 1024, 8192, 128, 0);
        float s[64], o[12];
        uint32_t pp[4 * PRING];
#pragma unroll 1
        for (int attempt = 0; attempt < 2; attempt++) {
            float m0 = -INFINITY, m1 = -INFINITY;
            const int nmax = attempt ? 16 : 1;
#pragma unroll 1
            for (int j = nmax - 1; j >= 0; j--) {
                mbar_wait(bar_kv + 8 * j, 0);
                wg_fence(); wgmma_qk_n128(s, dq, dK + j * (AT_TILE / 16)); wg_commit(); wg_wait<0>();
#pragma unroll
                for (int i = 0; i < 16; i++) {
                    m0 = fmaxf(m0, fmaxf(s[4 * i], s[4 * i + 1]));
                    m1 = fmaxf(m1, fmaxf(s[4 * i + 2], s[4 * i + 3]));
                }
            }
            m0 = fmaxf(m0, __shfl_xor_sync(~0u, m0, 1)); m0 = fmaxf(m0, __shfl_xor_sync(~0u, m0, 2));
            m1 = fmaxf(m1, __shfl_xor_sync(~0u, m1, 1)); m1 = fmaxf(m1, __shfl_xor_sync(~0u, m1, 2));
            const float room = attempt ? 0.f : 80.f;
            const float nm0 = -fmaf(m0, ALPHA, room), nm1 = -fmaf(m1, ALPHA, room);
            const float b0 = (126.f + nm0) * (1.f / 254.f), b1 = (126.f + nm1) * (1.f / 254.f);
#pragma unroll
            for (int i = 0; i < 12; i++) o[i] = 0.f;
            uint64_t dk = dK + AT_TILE / 16, dv = dV;
#pragma unroll 1
            for (int j = 1; j < 16; j++) {
                softmax_pv<0>(s, pp, o, nm0, nm1, b0, b1, dv, c254, c3);
                mbar_wait(bar_kv + 8 * j, 0);
                wg_fence(); wgmma_qk_n128(s, dq, dk); wg_commit(); wg_wait<0>();
                dk += AT_TILE / 16; dv += AT_TILE / 16;
            }
            softmax_pv<0>(s, pp, o, nm0, nm1, b0, b1, dv, c254, c3);
            wg_wait<0>();
            if (attempt) break;
            bool ok = (o[8] < 1e36f) && (o[10] < 1e36f);
#pragma unroll
            for (int i = 0; i < 8; i++) ok = ok && (fabsf(o[i]) < INFINITY);
            if (!wg_any(!ok, 1 + wg)) break;
        }
        const float r0 = 1.f / o[8], r1 = 1.f / o[10];
        uint8_t* op = g_o + ((size_t)((qq * 8 + tile) * 8 + (head >> 2)) * 8 + (head & 3) * 2) * 1024 + warp * 256 + lane * 4;
        *reinterpret_cast<uint32_t*>(op) = pack_bf16(o[0] * r0, o[1] * r0);
        *reinterpret_cast<uint32_t*>(op + 128) = pack_bf16(o[2] * r1, o[3] * r1);
        *reinterpret_cast<uint32_t*>(op + 1024) = pack_bf16(o[4] * r0, o[5] * r0);
        *reinterpret_cast<uint32_t*>(op + 1024 + 128) = pack_bf16(o[6] * r1, o[7] * r1);
        if (tid == 0) TL(2, 3 + qt);
        if (tid == 384) TL(2, 5 + qt);
    }
}

struct OutMaps { CUtensorMap wdown, wo; };
constexpr int OUT_STAGES = 8, OUT_STAGE_BYTES = 24576;
constexpr int OUT_SMEM = OUT_STAGES * OUT_STAGE_BYTES + 1024 + 256;

__device__ __forceinline__ void out_mainloop(float (&acc)[64], int nkb, uint32_t base, uint32_t bar_full, uint32_t bar_empty, int& it) {
#pragma unroll 1
    for (int kb = 0; kb < nkb; kb++, it++) {
        const int st = it % OUT_STAGES;
        mbar_wait(bar_full + 8 * st, (it / OUT_STAGES) & 1);
        const uint64_t da = make_desc(base + st * OUT_STAGE_BYTES, 1024, 128, 0);
        const uint64_t db = make_desc(base + st * OUT_STAGE_BYTES + 8192, 8192, 1024, 1);
        wg_fence();
#pragma unroll
        for (int k = 0; k < 4; k++) wgmma_ss_n128_bt(acc, da + k * 128, db + k * 128, (kb | k) != 0);
        wg_commit();
        if (kb > 0) {
            wg_wait<1>();
            if (threadIdx.x == 0) mbar_arrive(bar_empty + 8 * ((it - 1) % OUT_STAGES));
        }
    }
    wg_wait<0>();
    if (threadIdx.x == 0) mbar_arrive(bar_empty + 8 * ((it - 1) % OUT_STAGES));
}

__global__ void __launch_bounds__(160, 1) out_kernel(const __grid_constant__ OutMaps maps, const __nv_bfloat16* __restrict__ x,
                                                     __nv_bfloat16* __restrict__ out) {
    extern __shared__ uint8_t smem_raw[];
    const uint32_t sbase = (smem_u32(smem_raw) + 1023) & ~1023u;
    const uint32_t bar_full = sbase + OUT_STAGES * OUT_STAGE_BYTES, bar_empty = bar_full + 8 * OUT_STAGES;
    const int tid = threadIdx.x;
    const int wid = __shfl_sync(~0u, tid >> 5, 0);
    const int m64 = blockIdx.x >> 2, nb = blockIdx.x & 3;
    if (tid == 0) TL(3, 0);
    if (tid == 0) {
        for (int i = 0; i < OUT_STAGES; i++) { mbar_init(bar_full + 8 * i, 1); mbar_init(bar_empty + 8 * i, 1); }
        fence_mbar_init();
    }
    __syncthreads();
    if (wid == 4) {
        if (tid == 128) {
            prefetch_map(&maps.wdown); prefetch_map(&maps.wo);
            for (int it = 0; it < OUT_STAGES; it++) {
                const uint32_t dst = sbase + it * OUT_STAGE_BYTES + 8192, bar = bar_full + 8 * it;
                mbar_expect_tx(bar, OUT_STAGE_BYTES);
                for (int b = 0; b < 2; b++) tma_2d(dst + b * 8192, &maps.wdown, nb * 128 + b * 64, it * 64, bar);
            }
            pdl_wait();
            TL(3, 1);
            for (int it = 0; it < 36; it++) {
                const int st = it % OUT_STAGES;
                const uint32_t dst = sbase + st * OUT_STAGE_BYTES, bar = bar_full + 8 * st;
                if (it >= OUT_STAGES) {
                    mbar_wait(bar_empty + 8 * st, ((it / OUT_STAGES) & 1) ^ 1);
                    mbar_expect_tx(bar, OUT_STAGE_BYTES);
                    for (int b = 0; b < 2; b++) {
                        if (it < 28) tma_2d(dst + 8192 + b * 8192, &maps.wdown, nb * 128 + b * 64, it * 64, bar);
                        else tma_2d(dst + 8192 + b * 8192, &maps.wo, nb * 128 + b * 64, (it - 28) * 64, bar);
                    }
                }
                const uint8_t* a = it < 28 ? g_h + (size_t)(m64 * 28 + it) * 8192 : g_o + (size_t)(m64 * 8 + it - 28) * 8192;
                bulk_g2s(dst, a, 8192, bar);
            }
        }
    } else {
        const int lane = tid & 31, t = lane & 3;
        const int row = m64 * 64 + wid * 16 + (lane >> 2);
        const uint32_t* xp = reinterpret_cast<const uint32_t*>(x + (size_t)row * DM + nb * 128) + t;
        uint32_t xv[32];
#pragma unroll
        for (int i = 0; i < 16; i++) { xv[2 * i] = __ldg(xp + 4 * i); xv[2 * i + 1] = __ldg(xp + 8 * (DM / 2) + 4 * i); }
        float dn[64], sa[64];
        int it = 0;
        out_mainloop(dn, 28, sbase, bar_full, bar_empty, it);
        if (tid == 0) TL(3, 2);
        uint32_t gate[32];
#pragma unroll
        for (int kb = 0; kb < 8; kb++, it++) {
            const int st = it % OUT_STAGES;
            mbar_wait(bar_full + 8 * st, (it / OUT_STAGES) & 1);
            const uint64_t da = make_desc(sbase + st * OUT_STAGE_BYTES, 1024, 128, 0);
            const uint64_t db = make_desc(sbase + st * OUT_STAGE_BYTES + 8192, 8192, 1024, 1);
            wg_fence();
#pragma unroll
            for (int k = 0; k < 4; k++) wgmma_ss_n128_bt(sa, da + k * 128, db + k * 128, (kb | k) != 0);
            wg_commit();
#pragma unroll
            for (int i = 4 * kb; i < 4 * kb + 4; i++) {
                const uint32_t d2 = pack_bf16(dn[2 * i], dn[2 * i + 1]);
                const float d0 = bf_lo(d2), d1 = bf_hi(d2);
                gate[i] = pack_bf16(__fdividef(d0, 1.f + exp2_fast(-1.4426950408889634f * d0)),
                                    __fdividef(d1, 1.f + exp2_fast(-1.4426950408889634f * d1)));
            }
        }
        wg_wait<0>();
        if (tid == 0) TL(3, 3);
        uint32_t* op = reinterpret_cast<uint32_t*>(out + (size_t)row * DM + nb * 128) + t;
#pragma unroll
        for (int i = 0; i < 32; i++)
            op[(i & 1) * 8 * (DM / 2) + 4 * (i >> 1)] = add_bf16x2(xv[i], mul_bf16x2(pack_bf16(sa[2 * i], sa[2 * i + 1]), gate[i]));
        if (tid == 0) TL(3, 4);
    }
}

typedef CUresult (*EncodeFn)(CUtensorMap*, CUtensorMapDataType, cuuint32_t, void*, const cuuint64_t*, const cuuint64_t*,
                             const cuuint32_t*, const cuuint32_t*, CUtensorMapInterleave, CUtensorMapSwizzle,
                             CUtensorMapL2promotion, CUtensorMapFloatOOBfill);

void make_weight_map(EncodeFn fn, CUtensorMap* m, const void* p, int rows, int cols) {
    cuuint64_t dims[2] = {(cuuint64_t)cols, (cuuint64_t)rows};
    cuuint64_t strides[1] = {(cuuint64_t)cols * 2};
    cuuint32_t box[2] = {64, 64}, es[2] = {1, 1};
    fn(m, CU_TENSOR_MAP_DATA_TYPE_BFLOAT16, 2, const_cast<void*>(p), dims, strides, box, es, CU_TENSOR_MAP_INTERLEAVE_NONE,
       CU_TENSOR_MAP_SWIZZLE_128B, CU_TENSOR_MAP_L2_PROMOTION_L2_256B, CU_TENSOR_MAP_FLOAT_OOB_FILL_NONE);
}

template <typename... KArgs, typename... Args>
void launch(void (*kern)(KArgs...), int grid, int block, int smem, bool pdl, Args... args) {
    cudaLaunchConfig_t cfg = {};
    cfg.gridDim = dim3(grid); cfg.blockDim = dim3(block); cfg.dynamicSmemBytes = smem; cfg.stream = cudaStreamPerThread;
    cudaLaunchAttribute attr[1];
    attr[0].id = cudaLaunchAttributeProgrammaticStreamSerialization;
    attr[0].val.programmaticStreamSerializationAllowed = 1;
    cfg.attrs = attr; cfg.numAttrs = pdl ? 1 : 0;
    cudaLaunchKernelEx(&cfg, kern, KArgs(args)...);
}

}

extern "C" void kernel_launch(void* const* d_in, const int* in_sizes, int n_in, void* d_out, int out_size) {
    (void)in_sizes; (void)n_in; (void)out_size;
    const __nv_bfloat16* x = (const __nv_bfloat16*)d_in[0];
    static EncodeFn encode = nullptr;
    if (!encode) {
        void* fn = nullptr;
        cudaDriverEntryPointQueryResult q;
        cudaGetDriverEntryPoint("cuTensorMapEncodeTiled", &fn, cudaEnableDefault, &q);
        encode = (EncodeFn)fn;
        cudaFuncSetAttribute(proj_kernel, cudaFuncAttributeMaxDynamicSharedMemorySize, PJ_SMEM);
        cudaFuncSetAttribute(attn_kernel, cudaFuncAttributeMaxDynamicSharedMemorySize, AT_SMEM);
        cudaFuncSetAttribute(out_kernel, cudaFuncAttributeMaxDynamicSharedMemorySize, OUT_SMEM);
    }
    ProjMaps pm;
    make_weight_map(encode, &pm.wqkv, d_in[1], DM, 3 * DM);
    make_weight_map(encode, &pm.wgate, d_in[4], DM, FF);
    make_weight_map(encode, &pm.wup, d_in[5], DM, FF);
    OutMaps om;
    make_weight_map(encode, &om.wdown, d_in[6], FF, DM);
    make_weight_map(encode, &om.wo, d_in[2], DM, DM);

    launch(ln_kernel, SEQ / 16, 256, 0, false, x);
    launch(proj_kernel, 128, 384, PJ_SMEM, true, pm);
    launch(attn_kernel, 128, 512, AT_SMEM, true, 254.f, 0.0551716685295105f);
    launch(out_kernel, 128, 160, OUT_SMEM, true, om, x, (__nv_bfloat16*)d_out);
}
```

```cpp
#include <cuda_runtime.h>
#include <cuda_bf16.h>
#include <cuda.h>
#include <stdint.h>

namespace {

constexpr int SEQ = 2048, DM = 512, NH = 32, FF = 1792;

__device__ __align__(1024) uint8_t g_xn[SEQ * DM * 2];
__device__ __align__(1024) uint8_t g_q[NH * 2 * SEQ * 8 * 2];
__device__ __align__(1024) uint8_t g_kv[NH * 4 * SEQ * 8 * 2];
__device__ __align__(1024) uint8_t g_h[SEQ * FF * 2];
__device__ __align__(1024) uint8_t g_o[SEQ * DM * 2];
__device__ uint32_t g_hflag[128];
__device__ uint32_t g_oflag[256];

constexpr uint32_t SBASE = 1024;
__device__ __forceinline__ uint32_t smem_u32(const void* p) { return (uint32_t)__cvta_generic_to_shared(p); }
__device__ __forceinline__ void mbar_init(uint32_t bar, int cnt) {
    asm volatile("mbarrier.init.shared::cta.b64 [%0], %1;" ::"r"(bar), "r"(cnt) : "memory");
}
__device__ __forceinline__ void mbar_expect_tx(uint32_t bar, int bytes) {
    asm volatile("mbarrier.arrive.expect_tx.shared::cta.b64 _, [%0], %1;" ::"r"(bar), "r"(bytes) : "memory");
}
__device__ __forceinline__ void mbar_arrive(uint32_t bar) {
    asm volatile("mbarrier.arrive.shared::cta.b64 _, [%0];" ::"r"(bar) : "memory");
}
__device__ __forceinline__ void mbar_wait(uint32_t bar, int parity) {
    asm volatile(
        "{\n.reg .pred p;\n.reg .u32 c;\nmov.u32 c, 0;\n"
        "LW:\nmbarrier.try_wait.parity.shared::cta.b64 p, [%0], %1;\n@p bra LD;\n"
        "add.u32 c, c, 1;\nsetp.lt.u32 p, c, 4000000;\n@p bra LW;\ntrap;\nLD:\n}"
        ::"r"(bar), "r"(parity) : "memory");
}
__device__ __forceinline__ void fence_mbar_init() { asm volatile("fence.mbarrier_init.release.cluster;" ::: "memory"); }
__device__ __forceinline__ void fence_proxy_async() { asm volatile("fence.proxy.async;" ::: "memory"); }
__device__ __forceinline__ void bulk_g2s(uint32_t dst, const void* src, int bytes, uint32_t bar) {
    asm volatile("cp.async.bulk.shared::cluster.global.mbarrier::complete_tx::bytes [%0], [%1], %2, [%3];"
                 ::"r"(dst), "l"(src), "r"(bytes), "r"(bar) : "memory");
}
__device__ __forceinline__ void tma_2d(uint32_t dst, const CUtensorMap* map, int x, int y, uint32_t bar) {
    asm volatile("cp.async.bulk.tensor.2d.shared::cluster.global.mbarrier::complete_tx::bytes [%0], [%1, {%3, %4}], [%2];"
                 ::"r"(dst), "l"(map), "r"(bar), "r"(x), "r"(y) : "memory");
}
__device__ __forceinline__ void prefetch_map(const CUtensorMap* map) {
    asm volatile("prefetch.tensormap [%0];" ::"l"(map) : "memory");
}
__device__ __forceinline__ void pdl_wait() { asm volatile("griddepcontrol.wait;" ::: "memory"); }
__device__ __forceinline__ void pdl_launch() { asm volatile("griddepcontrol.launch_dependents;" ::: "memory"); }
__device__ __forceinline__ void wg_fence() { asm volatile("wgmma.fence.sync.aligned;" ::: "memory"); }
__device__ __forceinline__ void wg_commit() { asm volatile("wgmma.commit_group.sync.aligned;" ::: "memory"); }
template <int N> __device__ __forceinline__ void wg_wait() { asm volatile("wgmma.wait_group.sync.aligned %0;" ::"n"(N) : "memory"); }

__host__ __device__ constexpr uint64_t make_desc(uint32_t addr, uint32_t lbo, uint32_t sbo, uint32_t swz) {
    return (uint64_t)((addr & 0x3FFFF) >> 4) | ((uint64_t)(lbo >> 4) << 16) | ((uint64_t)(sbo >> 4) << 32) | ((uint64_t)swz << 62);
}
__device__ __forceinline__ uint32_t pack_bf16(float lo, float hi) {
    uint32_t r;
    asm("cvt.rn.bf16x2.f32 %0, %1, %2;" : "=r"(r) : "f"(hi), "f"(lo));
    return r;
}
__device__ __forceinline__ float bf_lo(uint32_t v) { return __uint_as_float(v << 16); }
__device__ __forceinline__ float bf_hi(uint32_t v) { return __uint_as_float(v & 0xFFFF0000u); }
__device__ __forceinline__ float round_bf16(float x) { return __bfloat162float(__float2bfloat16_rn(x)); }
__device__ __forceinline__ uint32_t mul_bf16x2(uint32_t a, uint32_t b) {
    uint32_t r;
    asm("mul.rn.bf16x2 %0, %1, %2;" : "=r"(r) : "r"(a), "r"(b));
    return r;
}
__device__ __forceinline__ uint32_t sub_bf16x2(uint32_t a, uint32_t b) {
    uint32_t r;
    asm("sub.rn.bf16x2 %0, %1, %2;" : "=r"(r) : "r"(a), "r"(b));
    return r;
}

__device__ __forceinline__ uint32_t add_bf16x2(uint32_t a, uint32_t b) {
    uint32_t r;
    asm("add.rn.bf16x2 %0, %1, %2;" : "=r"(r) : "r"(a), "r"(b));
    return r;
}
__device__ __forceinline__ float exp2_fast(float x) { float r; asm("ex2.approx.ftz.f32 %0, %1;" : "=f"(r) : "f"(x)); return r; }

__device__ __forceinline__ void bar_sync(int id, int n) { asm volatile("barrier.cta.sync.aligned %0, %1;" ::"r"(id), "r"(n) : "memory"); }
__device__ __forceinline__ void flag_add(uint32_t* p) {
    asm volatile("fence.acq_rel.gpu;\nred.relaxed.gpu.global.add.u32 [%0], 1;" ::"l"(p) : "memory");
}
__device__ __forceinline__ void flag_wait(const uint32_t* p, uint32_t target) {
    uint32_t v;
    for (int n = 0;; n++) {
        asm volatile("ld.acquire.gpu.global.u32 %0, [%1];" : "=r"(v) : "l"(p) : "memory");
        if (v >= target) break;
        if (n > 2000000) __trap();
        __nanosleep(64);
    }
}

__device__ __forceinline__ bool elect_one() {
    uint32_t p;
    asm volatile("{\n.reg .pred p;\nelect.sync _|p, 0xffffffff;\nselp.u32 %0, 1, 0, p;\n}" : "=r"(p));
    return p != 0;
}
__device__ __forceinline__ void prefetch_l2(const void* p, int bytes) {
    asm volatile("cp.async.bulk.prefetch.L2.global [%0], %1;" ::"l"(p), "r"(bytes) : "memory");
}

__device__ __forceinline__ void wgmma_ss_n192_bt(float (&d)[96], uint64_t da, uint64_t db, int acc) {
    asm volatile("{\n.reg .pred p;\nsetp.ne.b32 p, %98, 0;\n"
        "wgmma.mma_async.sync.aligned.m64n192k16.f32.bf16.bf16 {"
        "%0, %1, %2, %3, %4, %5, %6, %7, %8, %9, %10, %11, %12, %13, %14, %15, "
        "%16, %17, %18, %19, %20, %21, %22, %23, %24, %25, %26, %27, %28, %29, %30, %31, "
        "%32, %33, %34, %35, %36, %37, %38, %39, %40, %41, %42, %43, %44, %45, %46, %47, "
        "%48, %49, %50, %51, %52, %53, %54, %55, %56, %57, %58, %59, %60, %61, %62, %63, "
        "%64, %65, %66, %67, %68, %69, %70, %71, %72, %73, %74, %75, %76, %77, %78, %79, "
        "%80, %81, %82, %83, %84, %85, %86, %87, %88, %89, %90, %91, %92, %93, %94, %95"
        "}, %96, %97, p, 1, 1, 0, 1;\n}\n"
        :
        "+f"(d[0]), "+f"(d[1]), "+f"(d[2]), "+f"(d[3]), "+f"(d[4]), "+f"(d[5]), "+f"(d[6]), "+f"(d[7]),
        "+f"(d[8]), "+f"(d[9]), "+f"(d[10]), "+f"(d[11]), "+f"(d[12]), "+f"(d[13]), "+f"(d[14]), "+f"(d[15]),
        "+f"(d[16]), "+f"(d[17]), "+f"(d[18]), "+f"(d[19]), "+f"(d[20]), "+f"(d[21]), "+f"(d[22]), "+f"(d[23]),
        "+f"(d[24]), "+f"(d[25]), "+f"(d[26]), "+f"(d[27]), "+f"(d[28]), "+f"(d[29]), "+f"(d[30]), "+f"(d[31]),
        "+f"(d[32]), "+f"(d[33]), "+f"(d[34]), "+f"(d[35]), "+f"(d[36]), "+f"(d[37]), "+f"(d[38]), "+f"(d[39]),
        "+f"(d[40]), "+f"(d[41]), "+f"(d[42]), "+f"(d[43]), "+f"(d[44]), "+f"(d[45]), "+f"(d[46]), "+f"(d[47]),
        "+f"(d[48]), "+f"(d[49]), "+f"(d[50]), "+f"(d[51]), "+f"(d[52]), "+f"(d[53]), "+f"(d[54]), "+f"(d[55]),
        "+f"(d[56]), "+f"(d[57]), "+f"(d[58]), "+f"(d[59]), "+f"(d[60]), "+f"(d[61]), "+f"(d[62]), "+f"(d[63]),
        "+f"(d[64]), "+f"(d[65]), "+f"(d[66]), "+f"(d[67]), "+f"(d[68]), "+f"(d[69]), "+f"(d[70]), "+f"(d[71]),
        "+f"(d[72]), "+f"(d[73]), "+f"(d[74]), "+f"(d[75]), "+f"(d[76]), "+f"(d[77]), "+f"(d[78]), "+f"(d[79]),
        "+f"(d[80]), "+f"(d[81]), "+f"(d[82]), "+f"(d[83]), "+f"(d[84]), "+f"(d[85]), "+f"(d[86]), "+f"(d[87]),
        "+f"(d[88]), "+f"(d[89]), "+f"(d[90]), "+f"(d[91]), "+f"(d[92]), "+f"(d[93]), "+f"(d[94]), "+f"(d[95])
        : "l"(da), "l"(db), "r"(acc));
}
__device__ __forceinline__ void wgmma_ss_n128_bt(float (&d)[64], uint64_t da, uint64_t db, int acc) {
    asm volatile("{\n.reg .pred p;\nsetp.ne.b32 p, %66, 0;\n"
        "wgmma.mma_async.sync.aligned.m64n128k16.f32.bf16.bf16 {"
        "%0, %1, %2, %3, %4, %5, %6, %7, %8, %9, %10, %11, %12, %13, %14, %15, "
        "%16, %17, %18, %19, %20, %21, %22, %23, %24, %25, %26, %27, %28, %29, %30, %31, "
        "%32, %33, %34, %35, %36, %37, %38, %39, %40, %41, %42, %43, %44, %45, %46, %47, "
        "%48, %49, %50, %51, %52, %53, %54, %55, %56, %57, %58, %59, %60, %61, %62, %63"
        "}, %64, %65, p, 1, 1, 0, 1;\n}\n"
        :
        "+f"(d[0]), "+f"(d[1]), "+f"(d[2]), "+f"(d[3]), "+f"(d[4]), "+f"(d[5]), "+f"(d[6]), "+f"(d[7]),
        "+f"(d[8]), "+f"(d[9]), "+f"(d[10]), "+f"(d[11]), "+f"(d[12]), "+f"(d[13]), "+f"(d[14]), "+f"(d[15]),
        "+f"(d[16]), "+f"(d[17]), "+f"(d[18]), "+f"(d[19]), "+f"(d[20]), "+f"(d[21]), "+f"(d[22]), "+f"(d[23]),
        "+f"(d[24]), "+f"(d[25]), "+f"(d[26]), "+f"(d[27]), "+f"(d[28]), "+f"(d[29]), "+f"(d[30]), "+f"(d[31]),
        "+f"(d[32]), "+f"(d[33]), "+f"(d[34]), "+f"(d[35]), "+f"(d[36]), "+f"(d[37]), "+f"(d[38]), "+f"(d[39]),
        "+f"(d[40]), "+f"(d[41]), "+f"(d[42]), "+f"(d[43]), "+f"(d[44]), "+f"(d[45]), "+f"(d[46]), "+f"(d[47]),
        "+f"(d[48]), "+f"(d[49]), "+f"(d[50]), "+f"(d[51]), "+f"(d[52]), "+f"(d[53]), "+f"(d[54]), "+f"(d[55]),
        "+f"(d[56]), "+f"(d[57]), "+f"(d[58]), "+f"(d[59]), "+f"(d[60]), "+f"(d[61]), "+f"(d[62]), "+f"(d[63])
        : "l"(da), "l"(db), "r"(acc));
}
__device__ __forceinline__ void wgmma_pv_n24(float (&d)[12], uint32_t a0, uint32_t a1, uint32_t a2, uint32_t a3, uint64_t db) {
    asm volatile(
        "wgmma.mma_async.sync.aligned.m64n24k16.f32.bf16.bf16 {"
        "%0, %1, %2, %3, %4, %5, %6, %7, %8, %9, %10, %11"
        "}, {%12, %13, %14, %15}, %16, 1, 1, 1, 1;\n"
        :
        "+f"(d[0]), "+f"(d[1]), "+f"(d[2]), "+f"(d[3]), "+f"(d[4]), "+f"(d[5]), "+f"(d[6]), "+f"(d[7]),
        "+f"(d[8]), "+f"(d[9]), "+f"(d[10]), "+f"(d[11])
        : "r"(a0), "r"(a1), "r"(a2), "r"(a3), "l"(db));
}
__device__ __forceinline__ void wgmma_qk_n64(float (&d)[32], uint32_t a0, uint32_t a1, uint32_t a2, uint32_t a3, uint64_t db) {
    asm volatile(
        "wgmma.mma_async.sync.aligned.m64n64k16.f32.bf16.bf16 {"
        "%0, %1, %2, %3, %4, %5, %6, %7, %8, %9, %10, %11, %12, %13, %14, %15, "
        "%16, %17, %18, %19, %20, %21, %22, %23, %24, %25, %26, %27, %28, %29, %30, %31"
        "}, {%32, %33, %34, %35}, %36, 0, 1, 1, 0;\n"
        :
        "=f"(d[0]), "=f"(d[1]), "=f"(d[2]), "=f"(d[3]), "=f"(d[4]), "=f"(d[5]), "=f"(d[6]), "=f"(d[7]),
        "=f"(d[8]), "=f"(d[9]), "=f"(d[10]), "=f"(d[11]), "=f"(d[12]), "=f"(d[13]), "=f"(d[14]), "=f"(d[15]),
        "=f"(d[16]), "=f"(d[17]), "=f"(d[18]), "=f"(d[19]), "=f"(d[20]), "=f"(d[21]), "=f"(d[22]), "=f"(d[23]),
        "=f"(d[24]), "=f"(d[25]), "=f"(d[26]), "=f"(d[27]), "=f"(d[28]), "=f"(d[29]), "=f"(d[30]), "=f"(d[31])
        : "r"(a0), "r"(a1), "r"(a2), "r"(a3), "l"(db));
}

__global__ void __launch_bounds__(256) ln_kernel(const __nv_bfloat16* __restrict__ x) {
    pdl_launch();
    if (blockIdx.x == 0) {
        if (threadIdx.x < 128) g_hflag[threadIdx.x] = 0;
        g_oflag[threadIdx.x] = 0;
    }
    const int warp = threadIdx.x >> 5, lane = threadIdx.x & 31, l16 = lane & 15;
    const int row = blockIdx.x * 16 + warp * 2 + (lane >> 4);
    const uint4* xr = reinterpret_cast<const uint4*>(x + (size_t)row * DM);
    uint32_t v[16];
#pragma unroll
    for (int i = 0; i < 4; i++) {
        uint4 t = __ldg(xr + l16 + 16 * i);
        v[4 * i] = t.x; v[4 * i + 1] = t.y; v[4 * i + 2] = t.z; v[4 * i + 3] = t.w;
    }
    float sum = 0.f;
#pragma unroll
    for (int i = 0; i < 16; i++) sum += bf_lo(v[i]) + bf_hi(v[i]);
#pragma unroll
    for (int o = 1; o < 16; o <<= 1) sum += __shfl_xor_sync(~0u, sum, o);
    const float mean = sum * (1.f / DM);
    float sq = 0.f;
#pragma unroll
    for (int i = 0; i < 16; i++) {
        float a = bf_lo(v[i]) - mean, b = bf_hi(v[i]) - mean;
        sq = fmaf(a, a, sq); sq = fmaf(b, b, sq);
    }
#pragma unroll
    for (int o = 1; o < 16; o <<= 1) sq += __shfl_xor_sync(~0u, sq, o);
    const float var = round_bf16(sq * (1.f / DM));
    const float sd = round_bf16(sqrtf(round_bf16(var + round_bf16(1e-5f))));
    const float rs = 1.f / sd;
    const uint32_t mean2 = pack_bf16(mean, mean);
    uint8_t* dst = g_xn + (size_t)(row >> 6) * 65536 + ((row & 63) >> 3) * 128 + (row & 7) * 16;
#pragma unroll
    for (int i = 0; i < 4; i++) {
        uint32_t w[4];
#pragma unroll
        for (int k = 0; k < 4; k++) {
            uint32_t d = sub_bf16x2(v[4 * i + k], mean2);
            w[k] = pack_bf16(bf_lo(d) * rs, bf_hi(d) * rs);
        }
        const int j = l16 + 16 * i;
        *reinterpret_cast<uint4*>(dst + (size_t)j * 1024) = make_uint4(w[0], w[1], w[2], w[3]);
    }
}

constexpr int QK_STAGES = 5, QK_STAGE_BYTES = 16384 + 24576;
constexpr int QK_SMEM = QK_STAGES * QK_STAGE_BYTES + 256;

struct WeightPtrs { const uint8_t* p[4]; };
__global__ void __launch_bounds__(288, 1) qkv_kernel(const __grid_constant__ CUtensorMap wmap, WeightPtrs w) {
    extern __shared__ __align__(1024) uint8_t smem_raw[];
    constexpr uint32_t sbase = SBASE;
    constexpr uint32_t bar_full = sbase + QK_STAGES * QK_STAGE_BYTES, bar_empty = bar_full + 8 * QK_STAGES;
    const int tid = threadIdx.x;
    const int wg = __shfl_sync(~0u, tid >> 7, 0);
    const int mt = blockIdx.x & 15, g = blockIdx.x >> 4;
    if (tid == 0) {
        if (smem_u32(smem_raw) != SBASE) __trap();
        for (int i = 0; i < QK_STAGES; i++) { mbar_init(bar_full + 8 * i, 1); mbar_init(bar_empty + 8 * i, 2); }
        fence_mbar_init();
    }
    __syncthreads();
    if (wg == 2) {
        if (tid == 256) {
            prefetch_map(&wmap);
            for (int kb = 0; kb < QK_STAGES; kb++) {
                const uint32_t dst = sbase + kb * QK_STAGE_BYTES, bar = bar_full + 8 * kb;
                mbar_expect_tx(bar, QK_STAGE_BYTES);
                for (int b = 0; b < 3; b++) tma_2d(dst + 16384 + b * 8192, &wmap, b * DM + g * 64, kb * 64, bar);
            }
            pdl_wait();
            pdl_launch();
            for (int kb = 0; kb < 8; kb++) {
                const int st = kb % QK_STAGES;
                const uint32_t dst = sbase + st * QK_STAGE_BYTES, bar = bar_full + 8 * st;
                if (kb >= QK_STAGES) {
                    mbar_wait(bar_empty + 8 * st, 0);
                    mbar_expect_tx(bar, QK_STAGE_BYTES);
                    for (int b = 0; b < 3; b++) tma_2d(dst + 16384 + b * 8192, &wmap, b * DM + g * 64, kb * 64, bar);
                }
                for (int h = 0; h < 2; h++) bulk_g2s(dst + h * 8192, g_xn + (size_t)((mt * 2 + h) * 8 + kb) * 8192, 8192, bar);
                if (kb == QK_STAGES - 1) {
                    for (int i = 0; i < 4; i++) {
                        const int bytes = (i == 3 ? DM * DM : DM * FF) * 2 / 128;
                        prefetch_l2(w.p[i] + (size_t)blockIdx.x * bytes, bytes);
                    }
                }
            }
        }
    } else {
        float acc[96];
#pragma unroll 1
        for (int kb = 0; kb < 8; kb++) {
            const int st = kb % QK_STAGES;
            mbar_wait(bar_full + 8 * st, kb / QK_STAGES);
            const uint64_t da = make_desc(sbase + st * QK_STAGE_BYTES + wg * 8192, 1024, 128, 0);
            const uint64_t db = make_desc(sbase + st * QK_STAGE_BYTES + 16384, 8192, 1024, 1);
            wg_fence();
#pragma unroll
            for (int k = 0; k < 4; k++) wgmma_ss_n192_bt(acc, da + k * 128, db + k * 128, (kb | k) != 0);
            wg_commit();
            if (kb > 0) {
                wg_wait<1>();
                if ((tid & 127) == 0) mbar_arrive(bar_empty + 8 * ((kb - 1) % QK_STAGES));
            }
        }
        wg_wait<0>();
        const int lane = tid & 31, t = lane & 3;
        const int row = mt * 128 + wg * 64 + ((tid >> 5) & 3) * 16 + (lane >> 2);
        uint8_t* qp = g_q + (size_t)g * 4 * 65536 + row * 16 + t * 4;
        uint8_t* kv = g_kv + (size_t)g * 4 * 131072 + t * 4;
        uint8_t* p0 = kv + (row >> 7) * 4096 + (row & 127) * 16;
        uint8_t* p1 = kv + 65536 + row * 16;
#pragma unroll
        for (int i = 0; i < 24; i++) {
            const int type = i >> 3, hl = (i & 7) >> 1, half = i & 1;
            uint8_t* p = type == 0 ? qp + hl * 65536 + half * 32768
                                   : (half ? p1 + (type == 1 ? 32768 : 0) : p0 + (type == 1 ? 2048 : 0)) + hl * 131072;
            *reinterpret_cast<uint32_t*>(p) = pack_bf16(acc[4 * i], acc[4 * i + 1]);
            *reinterpret_cast<uint32_t*>(p + 128) = pack_bf16(acc[4 * i + 2], acc[4 * i + 3]);
        }
    }
}

constexpr float ALPHA = 0.25f * 1.4426950408889634f;
constexpr float MAGIC = 12582912.f;
#define POLY_MASK 0x0C0C0C0Cu
constexpr int FS_ONES = 131072, FS_RING = FS_ONES + 2048;
constexpr int FS_STAGES = 4, FS_STAGE_BYTES = 24576;
constexpr int FS_BAR = FS_RING + FS_STAGES * FS_STAGE_BYTES;
constexpr int FS_SMEM = FS_BAR + 160;
constexpr uint64_t DK_STEP = 256ull - (128ull << 16), DV_STEP = 256ull - (128ull << 32);

constexpr float BETA0 = 125.83138674911477f;
__device__ __forceinline__ float ex2_fma(float s, float beta, float c254) {
    float y;
    asm("fma.rn.sat.f32 %0, %1, %2, %3;" : "=f"(y) : "f"(s), "f"(ALPHA / 254.f), "f"(beta));
    const float t = fmaf(y, c254, MAGIC - 138.f);
    const float r = t - (MAGIC - 138.f);
    const float f = fmaf(y, 254.f, -r);
    float p = fmaf(f, c254, 1116.93603f);
    p = fmaf(p, f, 3191.64334f);
    p = fmaf(p, f, 4603.48101f);
    return __uint_as_float(__float_as_uint(p) + (__float_as_uint(t) << 23));
}
template <int KK>
__device__ __forceinline__ void softmax_pv(float (&s)[32], uint32_t (&pp)[16], float (&o)[12], float nm0, float nm1,
                                           float b0, float b1, uint64_t dv, float c254,
                                           uint32_t q0, uint32_t q1, uint32_t q2, uint32_t q3, uint64_t dk_next) {
    if constexpr (KK < 4) {
        float e[8];
#pragma unroll
        for (int i = 0; i < 8; i++) {
            const bool row1 = (i >> 1) & 1;
            const bool poly = (POLY_MASK >> (KK * 8 + i)) & 1;
            e[i] = poly ? ex2_fma(s[8 * KK + i], row1 ? b1 : b0, c254) : exp2_fast(fmaf(s[8 * KK + i], ALPHA, row1 ? nm1 : nm0));
        }
#pragma unroll
        for (int i = 0; i < 4; i++) pp[4 * KK + i] = pack_bf16(e[2 * i], e[2 * i + 1]);
        wg_fence();
        if constexpr (KK == 3) { wgmma_qk_n64(s, q0, q1, q2, q3, dk_next); wg_commit(); }
        wgmma_pv_n24(o, pp[4 * KK], pp[4 * KK + 1], pp[4 * KK + 2], pp[4 * KK + 3], dv + KK * 16);
        softmax_pv<KK + 1>(s, pp, o, nm0, nm1, b0, b1, dv, c254, q0, q1, q2, q3, dk_next);
    } else {
        wg_commit(); wg_wait<0>();
    }
}
__device__ __forceinline__ bool wg_any(bool pred, int bar_id) {
    uint32_t r;
    asm volatile("{\n.reg .pred p, q;\nsetp.ne.u32 p, %1, 0;\nbarrier.cta.red.or.aligned.pred q, %2, 128, p;\nselp.u32 %0, 1, 0, q;\n}"
                 : "=r"(r) : "r"((uint32_t)pred), "r"(bar_id) : "memory");
    return __shfl_sync(~0u, r, 0) != 0;
}

struct FusedMaps { CUtensorMap wgate, wup, wdown, wo, x; };

#define PACE_GU 1
#define PACE_DN 2
template <uint32_t STAGE, uint32_t BAR, int PACE = 4>
__device__ __forceinline__ void ffn_mma_at(float (&acc)[64], int parity, bool first) {
    mbar_wait(BAR, parity);
    constexpr uint64_t da = make_desc(STAGE, 1024, 128, 0), db = make_desc(STAGE + 8192, 8192, 1024, 1);
    wg_fence();
#pragma unroll
    for (int k = 0; k < 4; k++) {
        wgmma_ss_n128_bt(acc, da + k * 128, db + k * 128, !(first && k == 0));
        if (PACE < 4 && k % PACE == PACE - 1 && k < 3) { wg_commit(); wg_wait<0>(); wg_fence(); }
    }
    wg_commit();
}
template <int SLOT, int PACE>
__device__ __forceinline__ void ffn_mma(float (&acc)[64], uint32_t, uint32_t, int parity, bool first) {
    ffn_mma_at<SBASE + FS_RING + SLOT * FS_STAGE_BYTES, SBASE + FS_BAR + 40 + 8 * SLOT, PACE>(acc, parity, first);
}
__device__ __forceinline__ void ffn_load_a(uint32_t ring, uint32_t bar_full, int slot, const uint8_t* src) {
    if (elect_one()) {
        mbar_expect_tx(bar_full + 8 * slot, FS_STAGE_BYTES);
        bulk_g2s(ring + slot * FS_STAGE_BYTES, src, 8192, bar_full + 8 * slot);
    }
}
__device__ __forceinline__ void ffn_load_w(uint32_t ring, uint32_t bar_full, int slot, int role, const CUtensorMap* map, int x, int y) {
    if (elect_one()) tma_2d(ring + slot * FS_STAGE_BYTES + role * 8192, map, x, y, bar_full + 8 * slot);
}

__global__ void __launch_bounds__(640, 1) fused_kernel(const __grid_constant__ FusedMaps maps, __nv_bfloat16* __restrict__ out, float c254) {
    extern __shared__ __align__(1024) uint8_t smem_raw[];
    constexpr uint32_t sbase = SBASE;
    constexpr uint32_t bar_kv = sbase + FS_BAR, bar_full = bar_kv + 40, bar_go = bar_full + 8 * FS_STAGES;
    constexpr uint32_t ord_cnt = bar_go + 8, ord = ord_cnt + 8;
    constexpr uint32_t ring = sbase + FS_RING;
    const int tid = threadIdx.x;
    const int wg = __shfl_sync(~0u, tid >> 7, 0), warp = (tid >> 5) & 3, lane = tid & 31;
    if (tid == 0) {
        if (smem_u32(smem_raw) != SBASE) __trap();
        for (int i = 0; i < 5; i++) mbar_init(bar_kv + 8 * i, 1);
        for (int i = 0; i < FS_STAGES; i++) mbar_init(bar_full + 8 * i, 1);
        mbar_init(bar_go, 1);
        asm volatile("st.shared.u32 [%0], %1;" ::"r"(ord_cnt), "r"(0) : "memory");
        for (int i = 0; i < 8; i++) asm volatile("st.shared.u32 [%0], %1;" ::"r"(ord + 4 * i), "r"(0xFFFFFFFFu) : "memory");
        fence_mbar_init();
    }
    if (tid < 128) reinterpret_cast<uint4*>(smem_raw + FS_ONES)[tid] = make_uint4(0x3F803F80u, 0x3F803F80u, 0x3F803F80u, 0x3F803F80u);
    fence_proxy_async();
    __syncthreads();
    const int mb = blockIdx.x >> 2, qn = blockIdx.x & 3;

    if (wg < 4) {
        const int head = blockIdx.x >> 2, qq = blockIdx.x & 3;
        const uint64_t dK = make_desc(sbase + 2048, 96256, 128, 0);
        const uint64_t dV = make_desc(sbase, 128, 65536, 0);
        mbar_wait(bar_go, 0);
#pragma unroll 1
        for (int qt = 0; qt < 2; qt++) {
            const int tile = wg * 2 + qt;
            const uint32_t* qp = reinterpret_cast<const uint32_t*>(g_q + (size_t)head * 65536 + (qq * 512 + tile * 64 + warp * 16) * 16) + lane;
            const uint32_t q0 = __ldcg(qp), q1 = __ldcg(qp + 32), q2 = __ldcg(qp + 8192), q3 = __ldcg(qp + 8192 + 32);
            float s[32], o[12];
            uint32_t pp[16];
#pragma unroll 1
            for (int attempt = 0; attempt < 2; attempt++) {
                float m0 = -INFINITY, m1 = -INFINITY;
#pragma unroll 1
                for (int j = attempt ? 31 : 0; j >= 0; j--) {
                    mbar_wait(bar_kv + 8 * (j < 2 ? 0 : 1 + (j >> 3)), 0);
                    wg_fence(); wgmma_qk_n64(s, q0, q1, q2, q3, dK + (j >> 1) * DK_STEP + (j & 1) * 64); wg_commit(); wg_wait<0>();
#pragma unroll
                    for (int i = 0; i < 8; i++) {
                        m0 = fmaxf(m0, fmaxf(s[4 * i], s[4 * i + 1]));
                        m1 = fmaxf(m1, fmaxf(s[4 * i + 2], s[4 * i + 3]));
                    }
                }
                m0 = fmaxf(m0, __shfl_xor_sync(~0u, m0, 1)); m0 = fmaxf(m0, __shfl_xor_sync(~0u, m0, 2));
                m1 = fmaxf(m1, __shfl_xor_sync(~0u, m1, 1)); m1 = fmaxf(m1, __shfl_xor_sync(~0u, m1, 2));
                const float room = attempt ? 0.f : 90.f;
                const float nm0 = -fmaf(m0, ALPHA, room), nm1 = -fmaf(m1, ALPHA, room);
                const float b0 = (BETA0 + nm0) * (1.f / 254.f), b1 = (BETA0 + nm1) * (1.f / 254.f);
#pragma unroll
                for (int i = 0; i < 12; i++) o[i] = 0.f;
                uint64_t dk = dK, dv = dV;
#pragma unroll 1
                for (int j = 0; j < 16; j++) {
                    softmax_pv<0>(s, pp, o, nm0, nm1, b0, b1, dv, c254, q0, q1, q2, q3, dk + 64);
                    dk = j == 15 ? dK : dk + DK_STEP;
                    if (qt == 0 && j < 15) mbar_wait(bar_kv + 8 * (1 + ((j + 1) >> 2)), 0);
                    softmax_pv<0>(s, pp, o, nm0, nm1, b0, b1, dv + 64, c254, q0, q1, q2, q3, dk);
                    dv += DV_STEP;
                }
                if (attempt) break;
                bool ok = (o[8] < 1e36f) && (o[10] < 1e36f);
#pragma unroll
                for (int i = 0; i < 8; i++) ok = ok && (fabsf(o[i]) < INFINITY);
                if (!wg_any(!ok, 1 + wg)) break;
            }
            const float r0 = 1.f / o[8], r1 = 1.f / o[10];
            const int m64 = qq * 8 + tile;
            uint8_t* op = g_o + ((size_t)(m64 * 8 + (head >> 2)) * 8 + (head & 3) * 2) * 1024 + warp * 256 + lane * 4;
            *reinterpret_cast<uint32_t*>(op) = pack_bf16(o[0] * r0, o[1] * r0);
            *reinterpret_cast<uint32_t*>(op + 128) = pack_bf16(o[2] * r1, o[3] * r1);
            *reinterpret_cast<uint32_t*>(op + 1024) = pack_bf16(o[4] * r0, o[5] * r0);
            *reinterpret_cast<uint32_t*>(op + 1024 + 128) = pack_bf16(o[6] * r1, o[7] * r1);
        }
        bar_sync(1 + wg, 128);
        if ((tid & 127) == 0) {
            flag_add(&g_oflag[(qq * 8 + wg * 2) * 8 + (head >> 2)]);
            asm volatile("red.relaxed.gpu.global.add.u32 [%0], 1;" ::"l"(&g_oflag[(qq * 8 + wg * 2 + 1) * 8 + (head >> 2)]) : "memory");
        }
        if (tid >= 32) {
            asm volatile("barrier.cta.arrive.aligned 6, 640;" ::: "memory");
        } else {
            bar_sync(6, 640);
            if (lane < 8) {
                const uint32_t* flag = &g_oflag[mb * 8 + lane];
                const uint32_t bar = lane < 3 ? bar_full + 8 * lane : bar_kv + 8 * (lane - 3);
                const uint32_t dst = lane < 3 ? ring + lane * FS_STAGE_BYTES : lane < 7 ? sbase + (lane - 3) * FS_STAGE_BYTES : ring + 3 * FS_STAGE_BYTES + 16384;
                bool done = false;
                for (int n = 0; !done; n++) {
                    uint32_t v;
                    asm volatile("ld.acquire.gpu.global.u32 %0, [%1];" : "=r"(v) : "l"(flag) : "memory");
                    if (v >= 4) {
                        asm volatile("fence.proxy.async.global;" ::: "memory");
                        mbar_expect_tx(bar, FS_STAGE_BYTES);
                        bulk_g2s(dst, g_o + (mb * 8 + lane) * 8192, 8192, bar);
                        uint32_t pos;
                        asm volatile("atom.shared.add.u32 %0, [%1], 1;" : "=r"(pos) : "r"(ord_cnt) : "memory");
                        asm volatile("st.volatile.shared.u32 [%0], %1;" ::"r"(ord + 4 * pos), "r"(lane) : "memory");
                        done = true;
                    } else if (n > 2000000) {
                        __trap();
                    }
                }
            }
        }
    } else {
        const int role = __shfl_sync(~0u, warp, 0);
        const bool wrole = role == 1 || role == 2;
        const CUtensorMap* wmap = role == 2 ? &maps.wup : &maps.wgate;
        const uint8_t* asrc = g_xn + mb * 65536;
        uint4* gate_s = reinterpret_cast<uint4*>(smem_raw + FS_RING + 3 * FS_STAGE_BYTES) + (tid & 127);
        if (role == 1 && lane == 0) { prefetch_map(&maps.wgate); prefetch_map(&maps.wdown); }
        if (role == 2 && lane == 0) { prefetch_map(&maps.wup); prefetch_map(&maps.wo); }
        if (role == 3) pdl_wait();
        if (role == 3 && lane == 0) {
            mbar_arrive(bar_go);
            const uint8_t* src = g_kv + (size_t)(blockIdx.x >> 2) * 131072;
            for (int q = 0; q < 5; q++) {
                const int t0 = q == 0 ? 0 : q == 1 ? 1 : 4 * (q - 1), n = q == 0 ? 1 : q == 1 ? 3 : 4;
                mbar_expect_tx(bar_kv + 8 * q, n * 8192);
                bulk_g2s(sbase + t0 * 4096, src + t0 * 4096, n * 4096, bar_kv + 8 * q);
                bulk_g2s(sbase + 98304 + t0 * 2048, src + 98304 + t0 * 2048, n * 2048, bar_kv + 8 * q);
                bulk_g2s(sbase + 65536 + t0 * 2048, src + 65536 + t0 * 2048, n * 2048, bar_kv + 8 * q);
            }
        }
        __syncwarp();
        int fx = qn * 448;
#pragma unroll
        for (int i = 0; i < 3; i++) {
            if (role == 0) ffn_load_a(ring, bar_full, i, asrc + i * 8192);
            if (wrole) ffn_load_w(ring, bar_full, i, role, wmap, fx, i * 64);
        }
#pragma unroll 1
        for (int ft = 0; ft < 7; ft++) {
            float acc[64];
#pragma unroll
            for (int kb = 0; kb < 8; kb++) {
                switch (kb & 3) {
                    case 0: ffn_mma<0, PACE_GU>(acc, ring, bar_full, kb >> 2, kb == 0); break;
                    case 1: ffn_mma<1, PACE_GU>(acc, ring, bar_full, kb >> 2, false); break;
                    case 2: ffn_mma<2, PACE_GU>(acc, ring, bar_full, kb >> 2, false); break;
                    default: ffn_mma<3, PACE_GU>(acc, ring, bar_full, kb >> 2, false); break;
                }
                if (kb > 0) wg_wait<1>();
                const int nk = (kb + 3) & 7;
                if (kb + 3 < 8 || ft < 6) {
                    if (role == 0) ffn_load_a(ring, bar_full, (kb + 3) & 3, asrc + nk * 8192);
                    if (wrole) ffn_load_w(ring, bar_full, (kb + 3) & 3, role, wmap, kb + 3 < 8 ? fx : fx + 64, nk * 64);
                } else if (wrole) {
                    ffn_load_w(ring, bar_full, (kb + 3) & 3, role, &maps.wdown, qn * 128 + (role - 1) * 64, (qn * 7 + nk) * 64);
                }
            }
            wg_wait<0>();
            fx += 64;
            uint8_t* p = g_h + (size_t)(mb * 28 + qn * 7 + ft) * 8192 + warp * 256 + lane * 4;
#pragma unroll
            for (int i = 0; i < 8; i++) {
                *reinterpret_cast<uint32_t*>(p + i * 1024) =
                    mul_bf16x2(pack_bf16(acc[4 * i], acc[4 * i + 1]), pack_bf16(acc[4 * i + 32], acc[4 * i + 33]));
                *reinterpret_cast<uint32_t*>(p + i * 1024 + 128) =
                    mul_bf16x2(pack_bf16(acc[4 * i + 2], acc[4 * i + 3]), pack_bf16(acc[4 * i + 34], acc[4 * i + 35]));
            }
        }
        bar_sync(5, 128);
        if (tid == 512) flag_add(&g_hflag[blockIdx.x]);
        int ky = qn * 7 + 3;
        int ka = qn * 7;
        asrc = g_h + mb * (28 * 8192);
        if (role == 0) {
            if (lane < 4) flag_wait(&g_hflag[mb * 4 + lane], 1);
            __syncwarp();
            asm volatile("fence.proxy.async.global;" ::: "memory");
            for (int i = 0; i < 3; i++) { ffn_load_a(ring, bar_full, i, asrc + ka * 8192); ka = ka == 27 ? 0 : ka + 1; }
        }
        {
            float dn[64];
#pragma unroll 1
            for (int r = 0; r < 7; r++) {
#pragma unroll
                for (int k = 0; k < 4; k++) {
                    switch (k) {
                        case 0: ffn_mma<0, PACE_DN>(dn, ring, bar_full, r & 1, r == 0); break;
                        case 1: ffn_mma<1, PACE_DN>(dn, ring, bar_full, r & 1, false); break;
                        case 2: ffn_mma<2, PACE_DN>(dn, ring, bar_full, r & 1, false); break;
                        default: ffn_mma<3, PACE_DN>(dn, ring, bar_full, r & 1, false); break;
                    }
                    wg_wait<1>();
                    if (k == 0 || r < 6) {
                        if (role == 0) { ffn_load_a(ring, bar_full, (k + 3) & 3, asrc + ka * 8192); ka = ka == 27 ? 0 : ka + 1; }
                        if (wrole) ffn_load_w(ring, bar_full, (k + 3) & 3, role, &maps.wdown, qn * 128 + (role - 1) * 64, ky * 64);
                        ky = ky == 27 ? 0 : ky + 1;
                    } else if (wrole) {
                        ffn_load_w(ring, bar_full, (k + 3) & 3, role, &maps.wo, qn * 128 + (role - 1) * 64, (k - 1) * 64);
                    }
                }
            }
            wg_wait<0>();
            bar_sync(5, 128);
#pragma unroll
            for (int i4 = 0; i4 < 8; i4++) {
                uint32_t gt[4];
#pragma unroll
                for (int j = 0; j < 4; j++) {
                    const int i = 4 * i4 + j;
                    const uint32_t d2 = pack_bf16(dn[2 * i], dn[2 * i + 1]);
                    const float d0 = bf_lo(d2), d1 = bf_hi(d2);
                    gt[j] = pack_bf16(__fdividef(d0, 1.f + exp2_fast(-1.4426950408889634f * d0)),
                                      __fdividef(d1, 1.f + exp2_fast(-1.4426950408889634f * d1)));
                }
                gate_s[i4 * 128] = make_uint4(gt[0], gt[1], gt[2], gt[3]);
            }
        }
        bar_sync(6, 640);
        if (wrole) {
#pragma unroll
            for (int i = 0; i < 4; i++)
                if (elect_one()) tma_2d(sbase + i * FS_STAGE_BYTES + role * 8192, &maps.wo, qn * 128 + (role - 1) * 64, (3 + i) * 64, bar_kv + 8 * i);
            if (elect_one()) tma_2d(sbase + 114688 + (role - 1) * 8192, &maps.wo, qn * 128 + (role - 1) * 64, 7 * 64, bar_kv + 32);
        }
        if (role == 3 && elect_one()) {
            mbar_expect_tx(bar_go, 16384);
            tma_2d(sbase + 4 * FS_STAGE_BYTES, &maps.x, qn * 128, mb * 64, bar_go);
        }
        float sa[64];
#pragma unroll 1
        for (int n = 0; n < 8; n++) {
            uint32_t kb;
            for (int spin = 0;; spin++) {
                asm volatile("ld.volatile.shared.u32 %0, [%1];" : "=r"(kb) : "r"(ord + 4 * n) : "memory");
                if (kb < 8) break;
                if (spin > 100000000) __trap();
            }
            kb = __shfl_sync(~0u, kb, 0);
            const uint32_t a_addr = kb < 3 ? ring + kb * FS_STAGE_BYTES : kb < 7 ? sbase + (kb - 3) * FS_STAGE_BYTES : ring + 3 * FS_STAGE_BYTES + 16384;
            const uint32_t b_addr = kb < 7 ? a_addr + 8192 : sbase + 114688;
            mbar_wait(kb < 3 ? bar_full + 8 * kb : bar_kv + 8 * (kb - 3), 1);
            const uint64_t da = make_desc(a_addr, 1024, 128, 0), db = make_desc(b_addr, 8192, 1024, 1);
            wg_fence();
#pragma unroll
            for (int k = 0; k < 4; k++) wgmma_ss_n128_bt(sa, da + k * 128, db + k * 128, (n | k) != 0);
            wg_commit();
        }
        wg_wait<0>();
        uint32_t pr[32];
#pragma unroll
        for (int i4 = 0; i4 < 8; i4++) {
            const uint4 g4 = gate_s[i4 * 128];
            const uint32_t gt[4] = {g4.x, g4.y, g4.z, g4.w};
#pragma unroll
            for (int j = 0; j < 4; j++) pr[4 * i4 + j] = mul_bf16x2(pack_bf16(sa[8 * i4 + 2 * j], sa[8 * i4 + 2 * j + 1]), gt[j]);
        }
        constexpr int PITCH = 272;
        bar_sync(5, 128);
        const uint32_t stage = ring + FS_STAGE_BYTES + warp * 16 * PITCH;
        const uint32_t st_addr = stage + (((lane >> 3) & 1) * 8 + (lane & 7)) * PITCH + (lane >> 4) * 16;
#pragma unroll
        for (int j = 0; j < 8; j++)
            asm volatile("stmatrix.sync.aligned.m8n8.x4.shared.b16 [%0], {%1, %2, %3, %4};"
                         ::"r"(st_addr + j * 32), "r"(pr[4 * j]), "r"(pr[4 * j + 1]), "r"(pr[4 * j + 2]), "r"(pr[4 * j + 3]) : "memory");
        __syncwarp();
        mbar_wait(bar_go, 1);
        const size_t goff = (size_t)(mb * 64 + warp * 16 + (lane >> 4)) * DM + qn * 128 + (lane & 15) * 8;
        const uint32_t xs = sbase + 4 * FS_STAGE_BYTES + (warp * 16 + (lane >> 4)) * 256 + (lane & 15) * 16;
#pragma unroll
        for (int i = 0; i < 8; i++) {
            uint4 p, xv;
            asm volatile("ld.shared.v4.u32 {%0, %1, %2, %3}, [%4];" : "=r"(p.x), "=r"(p.y), "=r"(p.z), "=r"(p.w)
                         : "r"(stage + (2 * i + (lane >> 4)) * PITCH + (lane & 15) * 16));
            asm volatile("ld.shared.v4.u32 {%0, %1, %2, %3}, [%4];" : "=r"(xv.x), "=r"(xv.y), "=r"(xv.z), "=r"(xv.w) : "r"(xs + i * 512));
            *reinterpret_cast<uint4*>(out + goff + 2 * i * DM) =
                make_uint4(add_bf16x2(xv.x, p.x), add_bf16x2(xv.y, p.y), add_bf16x2(xv.z, p.z), add_bf16x2(xv.w, p.w));
        }
    }
}

typedef CUresult (*EncodeFn)(CUtensorMap*, CUtensorMapDataType, cuuint32_t, void*, const cuuint64_t*, const cuuint64_t*,
                             const cuuint32_t*, const cuuint32_t*, CUtensorMapInterleave, CUtensorMapSwizzle,
                             CUtensorMapL2promotion, CUtensorMapFloatOOBfill);

void make_weight_map(EncodeFn fn, CUtensorMap* m, const void* p, int rows, int cols) {
    cuuint64_t dims[2] = {(cuuint64_t)cols, (cuuint64_t)rows};
    cuuint64_t strides[1] = {(cuuint64_t)cols * 2};
    cuuint32_t box[2] = {64, 64}, es[2] = {1, 1};
    fn(m, CU_TENSOR_MAP_DATA_TYPE_BFLOAT16, 2, const_cast<void*>(p), dims, strides, box, es, CU_TENSOR_MAP_INTERLEAVE_NONE,
       CU_TENSOR_MAP_SWIZZLE_128B, CU_TENSOR_MAP_L2_PROMOTION_L2_256B, CU_TENSOR_MAP_FLOAT_OOB_FILL_NONE);
}

template <typename... KArgs, typename... Args>
void launch(void (*kern)(KArgs...), int grid, int block, int smem, bool pdl, Args... args) {
    cudaLaunchConfig_t cfg = {};
    cfg.gridDim = dim3(grid); cfg.blockDim = dim3(block); cfg.dynamicSmemBytes = smem; cfg.stream = cudaStreamPerThread;
    cudaLaunchAttribute attr[1];
    attr[0].id = cudaLaunchAttributeProgrammaticStreamSerialization;
    attr[0].val.programmaticStreamSerializationAllowed = 1;
    cfg.attrs = attr; cfg.numAttrs = pdl ? 1 : 0;
    cudaLaunchKernelEx(&cfg, kern, KArgs(args)...);
}

}

extern "C" void kernel_launch(void* const* d_in, const int* in_sizes, int n_in, void* d_out, int out_size) {
    (void)in_sizes; (void)n_in; (void)out_size;
    const __nv_bfloat16* x = (const __nv_bfloat16*)d_in[0];
    static EncodeFn encode = nullptr;
    if (!encode) {
        void* fn = nullptr;
        cudaDriverEntryPointQueryResult q;
        cudaGetDriverEntryPoint("cuTensorMapEncodeTiled", &fn, cudaEnableDefault, &q);
        encode = (EncodeFn)fn;
        cudaFuncSetAttribute(qkv_kernel, cudaFuncAttributeMaxDynamicSharedMemorySize, QK_SMEM);
        cudaFuncSetAttribute(fused_kernel, cudaFuncAttributeMaxDynamicSharedMemorySize, FS_SMEM);
    }
    CUtensorMap wqkv;
    make_weight_map(encode, &wqkv, d_in[1], DM, 3 * DM);
    FusedMaps fm;
    make_weight_map(encode, &fm.wgate, d_in[4], DM, FF);
    make_weight_map(encode, &fm.wup, d_in[5], DM, FF);
    make_weight_map(encode, &fm.wdown, d_in[6], FF, DM);
    make_weight_map(encode, &fm.wo, d_in[2], DM, DM);
    {
        cuuint64_t dims[2] = {(cuuint64_t)DM, (cuuint64_t)SEQ}, strides[1] = {(cuuint64_t)DM * 2};
        cuuint32_t box[2] = {128, 64}, es[2] = {1, 1};
        encode(&fm.x, CU_TENSOR_MAP_DATA_TYPE_BFLOAT16, 2, d_in[0], dims, strides, box, es, CU_TENSOR_MAP_INTERLEAVE_NONE,
               CU_TENSOR_MAP_SWIZZLE_NONE, CU_TENSOR_MAP_L2_PROMOTION_L2_256B, CU_TENSOR_MAP_FLOAT_OOB_FILL_NONE);
    }

    launch(ln_kernel, SEQ / 16, 256, 0, false, x);
    WeightPtrs wp{{(const uint8_t*)d_in[4], (const uint8_t*)d_in[5], (const uint8_t*)d_in[6], (const uint8_t*)d_in[2]}};
    launch(qkv_kernel, 128, 288, QK_SMEM, true, wqkv, wp);
    launch(fused_kernel, 128, 640, FS_SMEM, true, fm, (__nv_bfloat16*)d_out, 254.f);
}
```
